```python
import torch

def _softmax(x, axis=-1):
    return torch.softmax(x, dim=axis)
def _gelu(x):
    return torch.nn.functional.gelu(x, approximate="tanh")
def _silu(x):
    return torch.nn.functional.silu(x)
def _sigmoid(x):
    return torch.sigmoid(x)
def _layernorm(x, axis=-1, eps=1e-5):
    m = x.mean(dim=axis, keepdim=True)
    v = x.var(dim=axis, keepdim=True, unbiased=False)
    return (x - m) / torch.sqrt(v + eps)
def _scatter_add(tgt, idx, src, axis=0):
    return tgt.clone().index_add_(axis, idx, src)
def _segment_sum(src, seg, n):
    out = torch.zeros((n,) + src.shape[1:], dtype=src.dtype)
    return out.index_add_(0, seg, src)
def _pad(x, pw):
    flat = tuple(v for pair in reversed(pw) for v in pair)
    return torch.nn.functional.pad(x, flat)

kernel_name = 'recurrent_scan__linear_kernel_hedgehog__glu_gated_swiglu__prompt'

def setup_inputs():

    _w = (lambda a: (lambda t: t.to(torch.bfloat16) if t.is_floating_point() else t)(torch.as_tensor(a)))
    def _A_setup():
        B, S, D, H = 1, 2048, 512, 32
        Dh = D // H
        return {
            "x": _w((lambda *s: torch.randn(*s, dtype=torch.bfloat16) * 0.05)(B, S, D)),
            "wqkv": _w((lambda *s: torch.randn(*s, dtype=torch.bfloat16) * 0.8)(D, 3 * D)),
            "w_phi": _w((lambda *s: torch.randn(*s, dtype=torch.bfloat16) * 0.8)(H, Dh, Dh) * (Dh ** -0.5)),
            "wo": _w((lambda *s: torch.randn(*s, dtype=torch.bfloat16) * 0.8)(D, D)),
        }
    _A_in = _A_setup()

    def _B_setup():
        B, S, D, F = 1, 2048, 512, 1376
        return {
            "x": _w((lambda *s: torch.randn(*s, dtype=torch.bfloat16) * 0.05)(B, S, D)),
            "w1": _w((lambda *s: torch.randn(*s, dtype=torch.bfloat16) * 0.2)(D, F) * (2.0 / D) ** 0.5),
            "w3": _w((lambda *s: torch.randn(*s, dtype=torch.bfloat16) * 0.2)(D, F) * (2.0 / D) ** 0.5),
            "w2": _w((lambda *s: torch.randn(*s, dtype=torch.bfloat16) * 0.2)(F, D) * (2.0 / F) ** 0.5),
        }
    _B_in = _B_setup()

    return {
        "A_x": _A_in["x"],
        "A_wqkv": _A_in["wqkv"],
        "A_w_phi": _A_in["w_phi"],
        "A_wo": _A_in["wo"],
        "B_x": _B_in["x"],
        "B_w1": _B_in["w1"],
        "B_w3": _B_in["w3"],
        "B_w2": _B_in["w2"],
    }

def reference(A_x, A_wqkv, A_w_phi, A_wo, B_x, B_w1, B_w3, B_w2):
    def _A_ref(x, wqkv, w_phi, wo):
        B, S, D = x.shape
        H = 32; Dh = D // H
        qkv = (lambda x, *d: x.permute(*d))((x @ wqkv).reshape(B, S, 3, H, Dh), 2, 0, 3, 1, 4)
        q, k, v = qkv[0], qkv[1], qkv[2]
        pq = torch.einsum("bhsd,hdf->bhsf", q, w_phi)
        pk = torch.einsum("bhsd,hdf->bhsf", k, w_phi)
        phi_q = torch.concatenate([_softmax(pq, axis=-1), _softmax(-pq, axis=-1)], axis=-1)
        phi_k = torch.concatenate([_softmax(pk, axis=-1), _softmax(-pk, axis=-1)], axis=-1)
        kv = torch.einsum("bhsf,bhsd->bhfd", phi_k, v)
        z  = torch.einsum("bhsf->bhf", phi_k)
        num = torch.einsum("bhqf,bhfd->bhqd", phi_q, kv)
        den = torch.einsum("bhqf,bhf->bhq", phi_q, z)[..., None] + 1e-6
        o = num / den
        return (lambda x, *d: x.permute(*d))(o, 0, 2, 1, 3).reshape(B, S, D) @ wo

    def _B_ref(x, w1, w3, w2):
        gate = torch.einsum("bsd,df->bsf", x, w1)
        up = torch.einsum("bsd,df->bsf", x, w3)
        h = _silu(gate) * up
        out = torch.einsum("bsf,fd->bsd", h, w2)
        return out

    x = A_x
    xn = _layernorm(x, axis=-1)
    s = _A_ref(xn, A_wqkv, A_w_phi, A_wo)
    g = _silu(_B_ref(xn, B_w1, B_w3, B_w2))
    return x + s * g
```

```cpp
#include <cuda_runtime.h>
#include <cuda_bf16.h>
#include <cuda.h>
#include <stdint.h>

__device__ __forceinline__ void wgmma_n192(float (&d)[96], uint64_t da, uint64_t db, int scale_d) {
  asm volatile("{\n.reg .pred p;\nsetp.ne.b32 p, %98, 0;\n"
  "wgmma.mma_async.sync.aligned.m64n192k16.f32.bf16.bf16 {%0, %1, %2, %3, %4, %5, %6, %7, %8, %9, %10, %11, %12, %13, %14, %15, %16, %17, %18, %19, %20, %21, %22, %23, %24, %25, %26, %27, %28, %29, %30, %31, %32, %33, %34, %35, %36, %37, %38, %39, %40, %41, %42, %43, %44, %45, %46, %47, %48, %49, %50, %51, %52, %53, %54, %55, %56, %57, %58, %59, %60, %61, %62, %63, %64, %65, %66, %67, %68, %69, %70, %71, %72, %73, %74, %75, %76, %77, %78, %79, %80, %81, %82, %83, %84, %85, %86, %87, %88, %89, %90, %91, %92, %93, %94, %95}, %96, %97, p, 1, 1, 0, 1;\n}\n"
  : "+f"(d[0]), "+f"(d[1]), "+f"(d[2]), "+f"(d[3]), "+f"(d[4]), "+f"(d[5]), "+f"(d[6]), "+f"(d[7]), "+f"(d[8]), "+f"(d[9]), "+f"(d[10]), "+f"(d[11]), "+f"(d[12]), "+f"(d[13]), "+f"(d[14]), "+f"(d[15]), "+f"(d[16]), "+f"(d[17]), "+f"(d[18]), "+f"(d[19]), "+f"(d[20]), "+f"(d[21]), "+f"(d[22]), "+f"(d[23]), "+f"(d[24]), "+f"(d[25]), "+f"(d[26]), "+f"(d[27]), "+f"(d[28]), "+f"(d[29]), "+f"(d[30]), "+f"(d[31]), "+f"(d[32]), "+f"(d[33]), "+f"(d[34]), "+f"(d[35]), "+f"(d[36]), "+f"(d[37]), "+f"(d[38]), "+f"(d[39]), "+f"(d[40]), "+f"(d[41]), "+f"(d[42]), "+f"(d[43]), "+f"(d[44]), "+f"(d[45]), "+f"(d[46]), "+f"(d[47]), "+f"(d[48]), "+f"(d[49]), "+f"(d[50]), "+f"(d[51]), "+f"(d[52]), "+f"(d[53]), "+f"(d[54]), "+f"(d[55]), "+f"(d[56]), "+f"(d[57]), "+f"(d[58]), "+f"(d[59]), "+f"(d[60]), "+f"(d[61]), "+f"(d[62]), "+f"(d[63]), "+f"(d[64]), "+f"(d[65]), "+f"(d[66]), "+f"(d[67]), "+f"(d[68]), "+f"(d[69]), "+f"(d[70]), "+f"(d[71]), "+f"(d[72]), "+f"(d[73]), "+f"(d[74]), "+f"(d[75]), "+f"(d[76]), "+f"(d[77]), "+f"(d[78]), "+f"(d[79]), "+f"(d[80]), "+f"(d[81]), "+f"(d[82]), "+f"(d[83]), "+f"(d[84]), "+f"(d[85]), "+f"(d[86]), "+f"(d[87]), "+f"(d[88]), "+f"(d[89]), "+f"(d[90]), "+f"(d[91]), "+f"(d[92]), "+f"(d[93]), "+f"(d[94]), "+f"(d[95]) : "l"(da), "l"(db), "r"(scale_d));
}
__device__ __forceinline__ void wgmma_n128(float (&d)[64], uint64_t da, uint64_t db, int scale_d) {
  asm volatile("{\n.reg .pred p;\nsetp.ne.b32 p, %66, 0;\n"
  "wgmma.mma_async.sync.aligned.m64n128k16.f32.bf16.bf16 {%0, %1, %2, %3, %4, %5, %6, %7, %8, %9, %10, %11, %12, %13, %14, %15, %16, %17, %18, %19, %20, %21, %22, %23, %24, %25, %26, %27, %28, %29, %30, %31, %32, %33, %34, %35, %36, %37, %38, %39, %40, %41, %42, %43, %44, %45, %46, %47, %48, %49, %50, %51, %52, %53, %54, %55, %56, %57, %58, %59, %60, %61, %62, %63}, %64, %65, p, 1, 1, 0, 1;\n}\n"
  : "+f"(d[0]), "+f"(d[1]), "+f"(d[2]), "+f"(d[3]), "+f"(d[4]), "+f"(d[5]), "+f"(d[6]), "+f"(d[7]), "+f"(d[8]), "+f"(d[9]), "+f"(d[10]), "+f"(d[11]), "+f"(d[12]), "+f"(d[13]), "+f"(d[14]), "+f"(d[15]), "+f"(d[16]), "+f"(d[17]), "+f"(d[18]), "+f"(d[19]), "+f"(d[20]), "+f"(d[21]), "+f"(d[22]), "+f"(d[23]), "+f"(d[24]), "+f"(d[25]), "+f"(d[26]), "+f"(d[27]), "+f"(d[28]), "+f"(d[29]), "+f"(d[30]), "+f"(d[31]), "+f"(d[32]), "+f"(d[33]), "+f"(d[34]), "+f"(d[35]), "+f"(d[36]), "+f"(d[37]), "+f"(d[38]), "+f"(d[39]), "+f"(d[40]), "+f"(d[41]), "+f"(d[42]), "+f"(d[43]), "+f"(d[44]), "+f"(d[45]), "+f"(d[46]), "+f"(d[47]), "+f"(d[48]), "+f"(d[49]), "+f"(d[50]), "+f"(d[51]), "+f"(d[52]), "+f"(d[53]), "+f"(d[54]), "+f"(d[55]), "+f"(d[56]), "+f"(d[57]), "+f"(d[58]), "+f"(d[59]), "+f"(d[60]), "+f"(d[61]), "+f"(d[62]), "+f"(d[63]) : "l"(da), "l"(db), "r"(scale_d));
}
__device__ __forceinline__ void wgmma_n112(float (&d)[56], uint64_t da, uint64_t db, int scale_d) {
  asm volatile("{\n.reg .pred p;\nsetp.ne.b32 p, %58, 0;\n"
  "wgmma.mma_async.sync.aligned.m64n112k16.f32.bf16.bf16 {%0, %1, %2, %3, %4, %5, %6, %7, %8, %9, %10, %11, %12, %13, %14, %15, %16, %17, %18, %19, %20, %21, %22, %23, %24, %25, %26, %27, %28, %29, %30, %31, %32, %33, %34, %35, %36, %37, %38, %39, %40, %41, %42, %43, %44, %45, %46, %47, %48, %49, %50, %51, %52, %53, %54, %55}, %56, %57, p, 1, 1, 0, 1;\n}\n"
  : "+f"(d[0]), "+f"(d[1]), "+f"(d[2]), "+f"(d[3]), "+f"(d[4]), "+f"(d[5]), "+f"(d[6]), "+f"(d[7]), "+f"(d[8]), "+f"(d[9]), "+f"(d[10]), "+f"(d[11]), "+f"(d[12]), "+f"(d[13]), "+f"(d[14]), "+f"(d[15]), "+f"(d[16]), "+f"(d[17]), "+f"(d[18]), "+f"(d[19]), "+f"(d[20]), "+f"(d[21]), "+f"(d[22]), "+f"(d[23]), "+f"(d[24]), "+f"(d[25]), "+f"(d[26]), "+f"(d[27]), "+f"(d[28]), "+f"(d[29]), "+f"(d[30]), "+f"(d[31]), "+f"(d[32]), "+f"(d[33]), "+f"(d[34]), "+f"(d[35]), "+f"(d[36]), "+f"(d[37]), "+f"(d[38]), "+f"(d[39]), "+f"(d[40]), "+f"(d[41]), "+f"(d[42]), "+f"(d[43]), "+f"(d[44]), "+f"(d[45]), "+f"(d[46]), "+f"(d[47]), "+f"(d[48]), "+f"(d[49]), "+f"(d[50]), "+f"(d[51]), "+f"(d[52]), "+f"(d[53]), "+f"(d[54]), "+f"(d[55]) : "l"(da), "l"(db), "r"(scale_d));
}
__device__ __forceinline__ void wgmma_n32_tt(float (&d)[16], uint64_t da, uint64_t db, int scale_d) {
  asm volatile("{\n.reg .pred p;\nsetp.ne.b32 p, %18, 0;\n"
  "wgmma.mma_async.sync.aligned.m64n32k16.f32.bf16.bf16 {%0, %1, %2, %3, %4, %5, %6, %7, %8, %9, %10, %11, %12, %13, %14, %15}, %16, %17, p, 1, 1, 1, 1;\n}\n"
  : "+f"(d[0]), "+f"(d[1]), "+f"(d[2]), "+f"(d[3]), "+f"(d[4]), "+f"(d[5]), "+f"(d[6]), "+f"(d[7]), "+f"(d[8]), "+f"(d[9]), "+f"(d[10]), "+f"(d[11]), "+f"(d[12]), "+f"(d[13]), "+f"(d[14]), "+f"(d[15]) : "l"(da), "l"(db), "r"(scale_d));
}
__device__ __forceinline__ void wgmma_n8_tt(float (&d)[4], uint64_t da, uint64_t db, int scale_d) {
  asm volatile("{\n.reg .pred p;\nsetp.ne.b32 p, %6, 0;\n"
  "wgmma.mma_async.sync.aligned.m64n8k16.f32.bf16.bf16 {%0, %1, %2, %3}, %4, %5, p, 1, 1, 1, 1;\n}\n"
  : "+f"(d[0]), "+f"(d[1]), "+f"(d[2]), "+f"(d[3]) : "l"(da), "l"(db), "r"(scale_d));
}
__device__ __forceinline__ void wgmma_rs_n16(float (&d)[8], uint32_t a0, uint32_t a1, uint32_t a2, uint32_t a3, uint64_t db, int scale_d) {
  asm volatile("{\n.reg .pred p;\nsetp.ne.b32 p, %13, 0;\n"
  "wgmma.mma_async.sync.aligned.m64n16k16.f32.bf16.bf16 {%0, %1, %2, %3, %4, %5, %6, %7}, {%8, %9, %10, %11}, %12, p, 1, 1, 0;\n}\n"
  : "+f"(d[0]), "+f"(d[1]), "+f"(d[2]), "+f"(d[3]), "+f"(d[4]), "+f"(d[5]), "+f"(d[6]), "+f"(d[7]) : "r"(a0), "r"(a1), "r"(a2), "r"(a3), "l"(db), "r"(scale_d));
}
__device__ __forceinline__ void wgmma_rs_n24(float (&d)[12], uint32_t a0, uint32_t a1, uint32_t a2, uint32_t a3, uint64_t db, int scale_d) {
  asm volatile("{\n.reg .pred p;\nsetp.ne.b32 p, %17, 0;\n"
  "wgmma.mma_async.sync.aligned.m64n24k16.f32.bf16.bf16 {%0, %1, %2, %3, %4, %5, %6, %7, %8, %9, %10, %11}, {%12, %13, %14, %15}, %16, p, 1, 1, 0;\n}\n"
  : "+f"(d[0]), "+f"(d[1]), "+f"(d[2]), "+f"(d[3]), "+f"(d[4]), "+f"(d[5]), "+f"(d[6]), "+f"(d[7]), "+f"(d[8]), "+f"(d[9]), "+f"(d[10]), "+f"(d[11]) : "r"(a0), "r"(a1), "r"(a2), "r"(a3), "l"(db), "r"(scale_d));
}

namespace {

constexpr int S_ = 2048, D_ = 512, F_ = 1376;

constexpr uint32_t OFF_XN   = 0;
constexpr uint32_t OFF_Z    = 131072;
constexpr uint32_t OFF_H1   = OFF_Z;
constexpr uint32_t OFF_STG  = OFF_Z + 16384;
constexpr uint32_t OFF_KVB  = OFF_Z + 16384;
constexpr uint32_t OFF_MISC = OFF_Z + 98304;
constexpr uint32_t OFF_BAR  = OFF_MISC;
constexpr uint32_t OFF_ONES = OFF_MISC + 768;
constexpr uint32_t OFF_WPHI = OFF_MISC + 1024;
constexpr uint32_t SMEM_BYTES = OFF_MISC + 3072;

constexpr int B_FULL1 = 0, B_EMPTY1 = 8;
constexpr int B_FULLT = 16;
constexpr int B_EMPTYT = 44;
constexpr int B_H1 = 67, B_KV = 69, B_H2 = 71, B_O = 73;
constexpr int B_KVDONE = 75, B_KVB = 76, B_XO_OK = 77, B_XS_OK = 78, B_XO_FULL = 79, B_XS_FULL = 81;
constexpr int B_WPHI = 83, B_XNL = 84, B_XNR = 85, B_XLAND = 86, B_XFREE = 87, B_KVRAW = 88, B_H2RD = 89;
constexpr int NBAR = 90;
constexpr uint32_t OFF_KVRAW = OFF_Z + 24576;

__host__ __device__ constexpr uint32_t slot2_off(int s) {
  return s < 7 ? (uint32_t)s * 16384u : (s < 11 ? OFF_Z + 24576u + (uint32_t)(s - 7) * 16384u : OFF_H1);
}
constexpr uint32_t OFF_XS_RECV = OFF_Z + 24576;
constexpr uint32_t OFF_XO_RECV = OFF_Z + 57344;
__host__ __device__ constexpr int tile_slot(int t) {
  constexpr int tb[28] = {0, 1, 2, 3, 4, 7, 10, 8, 9, 11, 0, 1, 2, 3, 4, 7, 5, 8, 6, 11, 0, 1, 2, 3, 4, 5, 6, 11};
  return tb[t];
}
__host__ __device__ constexpr int tile_prev(int t) {
  constexpr int tb[28] = {-1, -1, -1, -1, -1, -1, -1, -1, -1, 0, 0, 1, 2, 3, 4, 5, 7, 7, 8, 9, 10, 11, 12, 13, 14, 16, 18, 19};
  return tb[t];
}
__device__ __constant__ signed char c_tile_slot[28] = {0, 1, 2, 3, 4, 7, 10, 8, 9, 11, 0, 1, 2, 3, 4, 7, 5, 8, 6, 11, 0, 1, 2, 3, 4, 5, 6, 11};
__device__ __constant__ signed char c_tile_prev[28] = {-1, -1, -1, -1, -1, -1, -1, -1, -1, 0, 0, 1, 2, 3, 4, 5, 7, 7, 8, 9, 10, 11, 12, 13, 14, 16, 18, 19};

__device__ __align__(1024) unsigned char g_ha[16 * 8 * 16384];
__device__ __align__(1024) unsigned char g_hb[16 * 8 * 16384];
__device__ __align__(1024) unsigned char g_hc[16 * 8 * 12288];
__device__ __align__(1024) unsigned char g_o [16 * 8 * 16384];
__device__ __align__(1024) float g_kv[2][32 * 512];
__device__ __align__(1024) float g_z [2][32 * 32];
__device__ unsigned int g_flag_ha[128 * 8];
__device__ unsigned int g_flag_hb[128 * 8];
__device__ unsigned int g_flag_o [128 * 8];
__device__ unsigned int g_kvcnt[8 * 8];
__device__ unsigned int g_epoch;
__device__ unsigned int g_done;

#define MARK(i)
#define TRC(i)
#define TRP(i)

struct TMaps {
  CUtensorMap qkv, w1, w3, w1p, w3p, w2, w2t, wo;
};

__device__ __forceinline__ uint32_t smem_u32(const void* p) { return (uint32_t)__cvta_generic_to_shared(p); }
__device__ __forceinline__ void mbar_init(uint32_t bar, int cnt) { asm volatile("mbarrier.init.shared::cta.b64 [%0], %1;" ::"r"(bar), "r"(cnt)); }
__device__ __forceinline__ void mbar_expect_tx(uint32_t bar, uint32_t bytes) { asm volatile("mbarrier.arrive.expect_tx.shared::cta.b64 _, [%0], %1;" ::"r"(bar), "r"(bytes) : "memory"); }
__device__ __forceinline__ void mbar_arrive(uint32_t bar) { asm volatile("mbarrier.arrive.shared::cta.b64 _, [%0];" ::"r"(bar) : "memory"); }
__device__ __forceinline__ void mbar_wait(uint32_t bar, uint32_t parity) {
  asm volatile("{\n.reg .pred p;\n.reg .u64 t, d;\n.reg .u32 a;\n"
               "WAIT_LOOP:\nmbarrier.try_wait.parity.shared::cta.b64 p, [%0], %1;\n@p bra WAIT_DONE;\n"
               "and.b32 a, %0, 0xFFFFFC00;\nld.shared.u64 d, [a + 1016];\nmov.u64 t, %%globaltimer;\nsetp.lt.u64 p, t, d;\n@p bra WAIT_LOOP;\nWAIT_DONE:\n}\n" ::"r"(bar), "r"(parity) : "memory");
}
__device__ __forceinline__ void mbar_wait_cluster(uint32_t bar, uint32_t parity) {
  asm volatile("{\n.reg .pred p;\n.reg .u64 t, d;\n.reg .u32 a;\n"
               "WAIT_LOOP:\nmbarrier.try_wait.parity.acquire.cluster.shared::cta.b64 p, [%0], %1;\n@p bra WAIT_DONE;\n"
               "and.b32 a, %0, 0xFFFFFC00;\nld.shared.u64 d, [a + 1016];\nmov.u64 t, %%globaltimer;\nsetp.lt.u64 p, t, d;\n@p bra WAIT_LOOP;\nWAIT_DONE:\n}\n" ::"r"(bar), "r"(parity) : "memory");
}
__device__ __forceinline__ unsigned long long gtime() { unsigned long long t; asm volatile("mov.u64 %0, %%globaltimer;" : "=l"(t)); return t; }
__device__ __forceinline__ uint32_t mapa(uint32_t addr, uint32_t cta) { uint32_t r; asm volatile("mapa.shared::cluster.u32 %0, %1, %2;" : "=r"(r) : "r"(addr), "r"(cta)); return r; }
__device__ __forceinline__ void mbar_arrive_remote(uint32_t raddr) { asm volatile("mbarrier.arrive.shared::cluster.b64 _, [%0];" ::"r"(raddr) : "memory"); }
__device__ __forceinline__ void tma2d(uint32_t dst, const CUtensorMap* tm, int c0, int c1, uint32_t bar) {
  asm volatile("cp.async.bulk.tensor.2d.shared::cluster.global.mbarrier::complete_tx::bytes [%0], [%1, {%3, %4}], [%2];" ::"r"(dst), "l"(tm), "r"(bar), "r"(c0), "r"(c1) : "memory");
}
__device__ __forceinline__ void tma3d(uint32_t dst, const CUtensorMap* tm, int c0, int c1, int c2, uint32_t bar) {
  asm volatile("cp.async.bulk.tensor.3d.shared::cluster.global.mbarrier::complete_tx::bytes [%0], [%1, {%3, %4, %5}], [%2];" ::"r"(dst), "l"(tm), "r"(bar), "r"(c0), "r"(c1), "r"(c2) : "memory");
}
__device__ __forceinline__ void pf2d(const CUtensorMap* tm, int c0, int c1) {
  asm volatile("cp.async.bulk.prefetch.tensor.2d.L2.global [%0, {%1, %2}];" ::"l"(tm), "r"(c0), "r"(c1) : "memory");
}
__device__ __forceinline__ void pf3d(const CUtensorMap* tm, int c0, int c1, int c2) {
  asm volatile("cp.async.bulk.prefetch.tensor.3d.L2.global [%0, {%1, %2, %3}];" ::"l"(tm), "r"(c0), "r"(c1), "r"(c2) : "memory");
}
__device__ __forceinline__ void bulk_g2s(uint32_t dst, const void* src, uint32_t bytes, uint32_t bar) {
  asm volatile("cp.async.bulk.shared::cluster.global.mbarrier::complete_tx::bytes [%0], [%1], %2, [%3];" ::"r"(dst), "l"(src), "r"(bytes), "r"(bar) : "memory");
}
__device__ __forceinline__ void bulk_s2g(void* dst, uint32_t src, uint32_t bytes) {
  asm volatile("cp.async.bulk.global.shared::cta.bulk_group [%0], [%1], %2;" ::"l"(dst), "r"(src), "r"(bytes) : "memory");
}
__device__ __forceinline__ void bulk_red_add_f32(void* dst, uint32_t src, uint32_t bytes) {
  asm volatile("cp.reduce.async.bulk.global.shared::cta.bulk_group.add.f32 [%0], [%1], %2;" ::"l"(dst), "r"(src), "r"(bytes) : "memory");
}
__device__ __forceinline__ void bulk_commit() { asm volatile("cp.async.bulk.commit_group;" ::: "memory"); }
__device__ __forceinline__ void bulk_wait0() { asm volatile("cp.async.bulk.wait_group 0;" ::: "memory"); }
__device__ __forceinline__ void fence_async_smem() { asm volatile("fence.proxy.async.shared::cta;" ::: "memory"); }
__device__ __forceinline__ void fence_async_all() { asm volatile("fence.proxy.async;" ::: "memory"); }
__device__ __forceinline__ void red_release_gpu(unsigned int* p, unsigned int v) { asm volatile("red.release.gpu.global.add.u32 [%0], %1;" ::"l"(p), "r"(v) : "memory"); }
__device__ __forceinline__ unsigned int ld_acquire_gpu(const unsigned int* p) { unsigned int v; asm volatile("ld.acquire.gpu.global.u32 %0, [%1];" : "=r"(v) : "l"(p) : "memory"); return v; }
__device__ __forceinline__ void wait_flag(const unsigned int* p, unsigned int target, uint32_t bar0) {
  while ((int)(ld_acquire_gpu(p) - target) < 0) {
    unsigned long long d; asm volatile("ld.shared.u64 %0, [%1 + 1016];" : "=l"(d) : "r"(bar0) : "memory");
    if (gtime() >= d) break;
  }
}
__device__ __forceinline__ void wg_fence() { asm volatile("wgmma.fence.sync.aligned;" ::: "memory"); }
__device__ __forceinline__ void wg_commit() { asm volatile("wgmma.commit_group.sync.aligned;" ::: "memory"); }
template <int N> __device__ __forceinline__ void wg_wait() { asm volatile("wgmma.wait_group.sync.aligned %0;" ::"n"(N) : "memory"); }
__device__ __forceinline__ void named_bar(int id, int n) { asm volatile("bar.sync %0, %1;" ::"r"(id), "r"(n) : "memory"); }
__device__ __forceinline__ uint64_t mkdesc(uint32_t addr, uint32_t lbo, uint32_t sbo, uint32_t mode) {
  return (uint64_t)((addr & 0x3FFFF) >> 4) | ((uint64_t)(lbo >> 4) << 16) | ((uint64_t)(sbo >> 4) << 32) | ((uint64_t)mode << 62);
}
__device__ __forceinline__ uint32_t pack_bf16(float lo, float hi) { uint32_t r; asm("cvt.rn.bf16x2.f32 %0, %1, %2;" : "=r"(r) : "f"(hi), "f"(lo)); return r; }
__device__ __forceinline__ float bf_lo(uint32_t v) { return __uint_as_float(v << 16); }
__device__ __forceinline__ float bf_hi(uint32_t v) { return __uint_as_float(v & 0xFFFF0000u); }
__device__ __forceinline__ float ex2(float x) { float r; asm("ex2.approx.ftz.f32 %0, %1;" : "=f"(r) : "f"(x)); return r; }
__device__ __forceinline__ float rcp(float x) { float r; asm("rcp.approx.ftz.f32 %0, %1;" : "=f"(r) : "f"(x)); return r; }
__device__ __forceinline__ float tanh_a(float x) { float r; asm("tanh.approx.f32 %0, %1;" : "=f"(r) : "f"(x)); return r; }
__device__ __forceinline__ float silu_mul(float g, float u) { float hg = 0.5f * g; float a = hg * u; return fmaf(a, tanh_a(hg), a); }
__device__ __forceinline__ void stsm4(uint32_t addr, uint32_t r0, uint32_t r1, uint32_t r2, uint32_t r3) {
  asm volatile("stmatrix.sync.aligned.m8n8.x4.shared.b16 [%0], {%1, %2, %3, %4};" ::"r"(addr), "r"(r0), "r"(r1), "r"(r2), "r"(r3) : "memory");
}
__device__ __forceinline__ void mma16816(float (&c)[4], uint32_t a0, uint32_t a1, uint32_t a2, uint32_t a3, uint32_t b0, uint32_t b1) {
  asm volatile("mma.sync.aligned.m16n8k16.row.col.f32.bf16.bf16.f32 {%0,%1,%2,%3}, {%4,%5,%6,%7}, {%8,%9}, {%0,%1,%2,%3};"
               : "+f"(c[0]), "+f"(c[1]), "+f"(c[2]), "+f"(c[3]) : "r"(a0), "r"(a1), "r"(a2), "r"(a3), "r"(b0), "r"(b1));
}
__device__ __forceinline__ uint32_t lds32(uint32_t a) { uint32_t v; asm volatile("ld.shared.u32 %0, [%1];" : "=r"(v) : "r"(a) : "memory"); return v; }
__device__ __forceinline__ void sts32(uint32_t a, uint32_t v) { asm volatile("st.shared.u32 [%0], %1;" ::"r"(a), "r"(v) : "memory"); }
__device__ __forceinline__ void sts16(uint32_t a, unsigned short v) { asm volatile("st.shared.u16 [%0], %1;" ::"r"(a), "h"(v) : "memory"); }
__device__ __forceinline__ void sts64f(uint32_t a, float x, float y) { asm volatile("st.shared.v2.f32 [%0], {%1, %2};" ::"r"(a), "f"(x), "f"(y) : "memory"); }
__device__ __forceinline__ void sts128(uint32_t a, uint4 v) { asm volatile("st.shared.v4.u32 [%0], {%1,%2,%3,%4};" ::"r"(a), "r"(v.x), "r"(v.y), "r"(v.z), "r"(v.w) : "memory"); }
__device__ __forceinline__ float4 lds128f(uint32_t a) { float4 v; asm volatile("ld.shared.v4.f32 {%0,%1,%2,%3}, [%4];" : "=f"(v.x), "=f"(v.y), "=f"(v.z), "=f"(v.w) : "r"(a) : "memory"); return v; }
__device__ __forceinline__ void st_async4(uint32_t raddr, float a, float b, float c, float d, uint32_t rbar) {
  asm volatile("st.async.weak.shared::cluster.mbarrier::complete_tx::bytes.v4.f32 [%0], {%1,%2,%3,%4}, [%5];" ::"r"(raddr), "f"(a), "f"(b), "f"(c), "f"(d), "r"(rbar) : "memory");
}
__device__ __forceinline__ uint4 ldg128(const void* p) { uint4 v; asm volatile("ld.global.nc.L1::no_allocate.v4.u32 {%0,%1,%2,%3}, [%4];" : "=r"(v.x), "=r"(v.y), "=r"(v.z), "=r"(v.w) : "l"(p)); return v; }

constexpr float LOG2E = 1.4426950408889634f;

__device__ __forceinline__ uint32_t mbar_test(uint32_t bar, uint32_t parity) {
  uint32_t ok;
  asm volatile("{\n.reg .pred p;\nmbarrier.test_wait.parity.shared::cta.b64 p, [%1], %2;\nselp.u32 %0, 1, 0, p;\n}\n" : "=r"(ok) : "r"(bar), "r"(parity) : "memory");
  return ok;
}
__device__ __forceinline__ void st_async4u(uint32_t raddr, uint4 v, uint32_t rbar) {
  asm volatile("st.async.weak.shared::cluster.mbarrier::complete_tx::bytes.v4.b32 [%0], {%1,%2,%3,%4}, [%5];" ::"r"(raddr), "r"(v.x), "r"(v.y), "r"(v.z), "r"(v.w), "r"(rbar) : "memory");
}
#define KEEPF(x) asm volatile("" ::"f"(x))

__device__ __forceinline__ void hh_both(const float (&p)[8], uint32_t (&ph)[8]) {
  const float* p0 = p; const float* p1 = p + 4;
  float mx[2], mn[2];
#pragma unroll
  for (int i = 0; i < 2; i++) {
    mx[i] = fmaxf(fmaxf(p0[2 * i], p0[2 * i + 1]), fmaxf(p1[2 * i], p1[2 * i + 1]));
    mn[i] = fminf(fminf(p0[2 * i], p0[2 * i + 1]), fminf(p1[2 * i], p1[2 * i + 1]));
  }
#pragma unroll
  for (int o = 1; o <= 2; o <<= 1) {
#pragma unroll
    for (int i = 0; i < 2; i++) {
      mx[i] = fmaxf(mx[i], __shfl_xor_sync(0xffffffffu, mx[i], o));
      mn[i] = fminf(mn[i], __shfl_xor_sync(0xffffffffu, mn[i], o));
    }
  }
  float e[2][4], f[2][4], sp[2], sn[2];
#pragma unroll
  for (int i = 0; i < 2; i++) {
    float mxl = -mx[i] * LOG2E, mnl = mn[i] * LOG2E;
    float v[4] = {p0[2 * i], p0[2 * i + 1], p1[2 * i], p1[2 * i + 1]};
#pragma unroll
    for (int c = 0; c < 4; c++) { e[i][c] = ex2(fmaf(v[c], LOG2E, mxl)); f[i][c] = ex2(fmaf(v[c], -LOG2E, mnl)); }
    sp[i] = (e[i][0] + e[i][1]) + (e[i][2] + e[i][3]);
    sn[i] = (f[i][0] + f[i][1]) + (f[i][2] + f[i][3]);
  }
#pragma unroll
  for (int o = 1; o <= 2; o <<= 1) {
#pragma unroll
    for (int i = 0; i < 2; i++) {
      sp[i] += __shfl_xor_sync(0xffffffffu, sp[i], o);
      sn[i] += __shfl_xor_sync(0xffffffffu, sn[i], o);
    }
  }
#pragma unroll
  for (int i = 0; i < 2; i++) {
    float rp = rcp(sp[i]), rn = rcp(sn[i]);
    ph[0 + i] = pack_bf16(e[i][0] * rp, e[i][1] * rp);
    ph[2 + i] = pack_bf16(e[i][2] * rp, e[i][3] * rp);
    ph[4 + i] = pack_bf16(f[i][0] * rn, f[i][1] * rn);
    ph[6 + i] = pack_bf16(f[i][2] * rn, f[i][3] * rn);
  }
}

template <int TA, int TB, int NK, int FIRST>
__device__ __forceinline__ void p2_issue(float (&acc)[64], uint32_t sb, uint32_t bar0, uint32_t aoff) {
  uint32_t aaddr = aoff;
  if (TA >= 0) {
    mbar_wait(bar0 + 8u * (B_FULLT + (TA < 0 ? 0 : TA)), 0);
    aaddr = sb + slot2_off(tile_slot(TA < 0 ? 0 : TA)) + aoff;
  }
  mbar_wait(bar0 + 8u * (B_FULLT + TB), 0);
  uint64_t dA = mkdesc(aaddr, 128, 256, 0), dB = mkdesc(sb + slot2_off(tile_slot(TB)), 8192, 1024, 1);
  wg_fence();
  wgmma_n128(acc, dA, dB, FIRST ? 0 : 1);
  wgmma_n128(acc, dA + 128, dB + 128, 1);
  wgmma_n128(acc, dA + 256, dB + 256, 1);
  if (NK > 3) wgmma_n128(acc, dA + 384, dB + 384, 1);
}
template <int RA, int RB, int WAITPREV>
__device__ __forceinline__ void p2_commit(uint32_t bar0, int lane) {
  wg_commit();
  if (WAITPREV) {
    wg_wait<1>();
    if (lane == 0) {
      if (RA >= 0) mbar_arrive(bar0 + 8u * (B_EMPTYT + (RA < 0 ? 0 : RA)));
      if (RB >= 0) mbar_arrive(bar0 + 8u * (B_EMPTYT + (RB < 0 ? 0 : RB)));
    }
  }
}
template <int TA, int TB, int NK, int FIRST, int RA, int RB, int WAITPREV>
__device__ __forceinline__ void p2_step(float (&acc)[64], uint32_t sb, uint32_t bar0, uint32_t aoff, int lane) {
  p2_issue<TA, TB, NK, FIRST>(acc, sb, bar0, aoff);
  p2_commit<RA, RB, WAITPREV>(bar0, lane);
}

__device__ __forceinline__ void teardown(bool leader) {
  asm volatile("barrier.cluster.arrive.release.aligned;\nbarrier.cluster.wait.acquire.aligned;" ::: "memory");
  if (leader) {
    __threadfence();
    unsigned int tk = atomicAdd(&g_done, 1u);
    if ((tk & 127u) == 127u) { atomicAdd(&g_epoch, 1u); }
  }
}

__global__ void __cluster_dims__(2, 1, 1) __launch_bounds__(384, 1)
fused_kernel(const __grid_constant__ TMaps tm, const __nv_bfloat16* __restrict__ x, const __nv_bfloat16* __restrict__ wphi,
             __nv_bfloat16* __restrict__ out) {
  extern __shared__ __align__(1024) unsigned char smem_raw[];
  const uint32_t sb = smem_u32(smem_raw);
  const int tid = threadIdx.x;
  const int warp = tid >> 5, lane = tid & 31;
  const int bid = blockIdx.x;
  const int m = bid >> 3, r = bid & 7, nq = r >> 1, kh = r & 1;
  const int sl = kh * 4 + nq;
  const int f0 = kh * 688 + nq * 176;
  const uint32_t bar0 = sb + OFF_BAR;
  auto BAR = [&](int i) { return bar0 + 8u * (uint32_t)i; };

  if (tid == 128) asm volatile("st.shared.u64 [%0 + 1016], %1;" ::"r"(bar0), "l"(gtime() + 2000000ull) : "memory");
  if (tid < NBAR) {
    int cnt = 1;
    if (tid >= B_EMPTY1 && tid < B_EMPTY1 + 8) cnt = 8;
    else if (tid >= B_EMPTYT && tid < B_EMPTYT + 23) cnt = 8;
    else if (tid >= B_H1 && tid < B_KVDONE) cnt = 128;
    else if (tid == B_KVDONE || tid == B_H2RD) cnt = 2;
    else if (tid == B_KVB || tid == B_WPHI) cnt = 32;
    else if (tid == B_XO_OK || tid == B_XS_OK || tid == B_XLAND || tid == B_XFREE) cnt = 8;
    else if (tid == B_XNL) cnt = 256;
    mbar_init(BAR(tid), cnt);
    if (tid == B_XNR) mbar_expect_tx(BAR(B_XNR), 65536);
    if (tid >= B_XO_FULL && tid < B_XO_FULL + 4) mbar_expect_tx(BAR(tid), 16384);
    asm volatile("fence.mbarrier_init.release.cluster;" ::: "memory");
  }
  __syncthreads();
  asm volatile("barrier.cluster.arrive.release.aligned;" ::: "memory");

  if (warp >= 8) {
    asm volatile("setmaxnreg.dec.sync.aligned.u32 40;");
    asm volatile("barrier.cluster.wait.acquire.aligned;" ::: "memory");
    if (warp == 8) {
      if (lane == 0) {
        MARK(0);
        mbar_wait(BAR(B_XLAND), 0);
        for (int j = 0; j < 16; j++) {
          if (j >= 4) mbar_wait(BAR(B_EMPTY1 + ((j - 4) & 7)), ((j - 4) >> 3) & 1);
          uint32_t dst = sb + OFF_Z + (uint32_t)((j + 2) & 3) * 20480u;
          uint32_t fb = BAR(B_FULL1 + (j & 7));
          mbar_expect_tx(fb, 20480);
          tma3d(dst, &tm.qkv, sl * 64, j * 32, 0, fb);
          tma2d(dst + 12288, &tm.w1, f0, j * 32, fb);
          tma2d(dst + 16384, &tm.w3, f0, j * 32, fb);
        }
        MARK(1);
        {
          auto unit = [&](int u, int slot) {
            uint32_t dst = sb + OFF_Z + 40960u + (uint32_t)slot * 8192u;
            uint32_t fb = BAR(B_FULL1 + ((16 + (u >> 1)) & 7));
            if (!(u & 1)) mbar_expect_tx(fb, 16384);
            if (u < 30) tma3d(dst, (u & 1) ? &tm.w3p : &tm.w1p, f0 + 64, (u >> 1) * 32, 0, fb);
            else {
              tma2d(dst, (u & 1) ? &tm.w3 : &tm.w1, f0 + 64, 480, fb);
              tma2d(dst + 4096, (u & 1) ? &tm.w3 : &tm.w1, f0 + 128, 480, fb);
            }
          };
          unit(0, 5);
          int slot = 6;
          for (int i = 0; i < 16; i++) {
            if (i == 0) { unit(1, 6); mbar_wait(BAR(B_EMPTY1 + (12 & 7)), 1); unit(2, 0); slot = 1; continue; }
            if (i == 1) { unit(3, 1); mbar_wait(BAR(B_EMPTY1 + (13 & 7)), 1); unit(4, 2); slot = 3; continue; }
            TRP(4 * i);
            if (i >= 3) mbar_wait(BAR(B_EMPTY1 + ((13 + i) & 7)), ((13 + i) >> 3) & 1);
            TRP(4 * i + 1);
            unit(2 * i + 1, slot); slot = (slot == 6) ? 0 : slot + 1;
            if (i < 15) { unit(2 * i + 2, slot); slot = (slot == 6) ? 0 : slot + 1; }
          }
        }
        MARK(2);
        const int colk = nq * 128 + kh * 64, cols = nq * 128 + (kh ^ 1) * 64;
        auto load_B = [&](int t, const CUtensorMap* mp, int row, uint32_t bytes) {
          int pv = c_tile_prev[t];
          if (pv >= 0) mbar_wait(BAR(B_EMPTYT + pv), 0);
          if (t == 16) mbar_wait(BAR(B_H2RD), 0);
          uint32_t dst = sb + slot2_off(c_tile_slot[t]); uint32_t fb = BAR(B_FULLT + t);
          mbar_expect_tx(fb, bytes);
          tma2d(dst, mp, colk, row, fb);
          tma2d(dst + 8192, mp, cols, row, fb);
        };
        auto frow = [&](int d) { return kh * 688 + ((nq + d) & 3) * 176; };
        mbar_wait(BAR(B_XFREE), 0);
        load_B(0, &tm.w2, frow(0), 16384);
        load_B(2, &tm.w2, frow(1), 16384);
        load_B(4, &tm.w2, frow(2), 16384);
        mbar_wait(BAR(B_EMPTY1 + (30 & 7)), 1);
        load_B(6, &tm.w2, frow(3), 16384);
        load_B(8, &tm.w2t, frow(0) + 128, 12288);
        mbar_wait(BAR(B_EMPTY1 + (31 & 7)), 1);
        load_B(7, &tm.w2, frow(0) + 64, 16384);
        MARK(3);
        for (int d = 1; d < 4; d++) {
          load_B(6 + 4 * d, &tm.w2, frow(d) + 64, 16384);
          load_B(8 + 4 * d, &tm.w2t, frow(d) + 128, 12288);
        }
        MARK(4);
        for (int d = 0; d < 4; d++) load_B(21 + 2 * d, &tm.wo, (kh * 4 + ((nq + d) & 3)) * 64, 16384);
        MARK(5);
      }
    } else if (warp == 9 || warp == 10) {
      if (lane == 0) {
        const int w = warp - 9;
        const unsigned int epoch = *(volatile unsigned int*)&g_epoch;
        const int id = m * 8 + sl;
        mbar_wait(BAR(B_H1 + w), 0);
        bulk_s2g(g_ha + (size_t)id * 16384 + w * 8192, sb + OFF_H1 + w * 8192, 8192);
        bulk_commit(); bulk_wait0();
        red_release_gpu(g_flag_ha + id * 8, 1);
        MARK(1);
        mbar_wait(BAR(B_KV + w), 0);
        bulk_red_add_f32(&g_kv[epoch & 1][sl * 2048], sb + OFF_STG + w * 12288, 8192);
        bulk_red_add_f32(&g_z[epoch & 1][sl * 128], sb + OFF_STG + w * 12288 + 8192, 512);
        bulk_commit(); bulk_wait0();
        red_release_gpu(g_kvcnt + sl * 8, 1);
        mbar_arrive(BAR(B_KVDONE));
        MARK(2);
        mbar_wait(BAR(B_H2 + w), 0);
        bulk_s2g(g_hb + (size_t)id * 16384 + w * 8192, sb + OFF_XN + 5 * 16384 + w * 8192, 8192);
        bulk_s2g(g_hc + (size_t)id * 12288 + w * 6144, sb + OFF_XN + 6 * 16384 + w * 8192, 6144);
        bulk_commit(); bulk_wait0();
        red_release_gpu(g_flag_hb + id * 8, 1);
        mbar_arrive(BAR(B_H2RD));
        MARK(3);
        mbar_wait(BAR(B_O + w), 0);
        bulk_s2g(g_o + (size_t)id * 16384 + w * 8192, sb + OFF_XN + 7 * 16384 + w * 8192, 8192);
        bulk_commit(); bulk_wait0();
        red_release_gpu(g_flag_o + id * 8, 1);
        MARK(4);
      }
    } else {
      {
        sts32(sb + OFF_ONES + lane * 4, 0x3F803F80u);
        const unsigned short* wp = reinterpret_cast<const unsigned short*>(wphi) + sl * 4 * 256;
#pragma unroll 8
        for (int i = lane; i < 1024; i += 32) {
          int h = i >> 8, d = (i >> 4) & 15, f = i & 15;
          sts16(sb + OFF_WPHI + h * 512 + (f >> 3) * 256 + (d >> 3) * 128 + (f & 7) * 16 + (d & 7) * 2, wp[i]);
        }
        fence_async_smem();
        mbar_arrive(BAR(B_WPHI));
      }
      const unsigned int epoch = *(volatile unsigned int*)&g_epoch;
      reinterpret_cast<float4*>(&g_kv[(epoch + 1) & 1][bid * 128])[lane] = make_float4(0.f, 0.f, 0.f, 0.f);
      if (lane < 8) g_z[(epoch + 1) & 1][bid * 8 + lane] = 0.f;
      if (lane == 0) {
        mbar_wait(BAR(B_XLAND), 0);
        pf3d(&tm.qkv, sl * 64, m * 32, 0);
        pf2d(&tm.w1, f0, m * 32);       pf2d(&tm.w3, f0, m * 32);
        __nanosleep(700);
        pf2d(&tm.w1, f0 + 64, m * 32);  pf2d(&tm.w3, f0 + 64, m * 32);
        pf2d(&tm.w1, f0 + 128, m * 32); pf2d(&tm.w3, f0 + 128, m * 32);
        __nanosleep(700);
        for (int i = bid; i < 240; i += 128) {
          if (i < 176) pf2d(&tm.w2, (i & 7) * 64, (i >> 3) * 64);
          else pf2d(&tm.wo, (i & 7) * 64, ((i - 176) >> 3) * 64);
        }
      }
      __syncwarp();
      const int grp = lane / 3, d = lane - grp * 3 + 1;
      const int id = m * 8 + kh * 4 + ((nq + d) & 3);
      int tile = grp == 0 ? 2 * d - 1 : (grp == 1 ? 5 + 4 * d : (grp == 2 ? 7 + 4 * d : 20 + 2 * d));
      const unsigned char* src = grp == 0 ? g_ha + (size_t)id * 16384 : (grp == 1 ? g_hb + (size_t)id * 16384 : (grp == 2 ? g_hc + (size_t)id * 12288 : g_o + (size_t)id * 16384));
      const unsigned int* flag = grp == 0 ? g_flag_ha + id * 8 : (grp == 3 ? g_flag_o + id * 8 : g_flag_hb + id * 8);
      unsigned int tgt = 2u * (epoch + 1u);
      if (lane == 12) { flag = g_kvcnt + sl * 8; tgt = 32u * (epoch + 1u); }
      if (lane > 11) tile = 9;
      const int pv = c_tile_prev[tile];
      const uint32_t wb = pv >= 0 ? BAR(B_EMPTYT + pv) : (tile == 5 ? BAR(B_KVB) : BAR(B_XFREE));
      int state = lane <= 12 ? 0 : 2;
      while (true) {
        if (state == 0 && (int)(ld_acquire_gpu(flag) - tgt) >= 0) state = 1;
        if (state == 1 && lane < 12 && mbar_test(wb, 0) && (tile != 9 || mbar_test(BAR(B_KVDONE), 0))) {
          uint32_t bytes = grp == 2 ? 12288u : 16384u;
          uint32_t fb = BAR(B_FULLT + tile);
          mbar_expect_tx(fb, bytes);
          bulk_g2s(sb + slot2_off(c_tile_slot[tile]), src, bytes, fb);
          state = 2;
        }
        unsigned kvrdy = __ballot_sync(0xffffffffu, lane == 12 && state == 1);
        if (kvrdy) {
          MARK(1);
          if (lane == 0) {
            mbar_expect_tx(BAR(B_KVRAW), 8704);
            bulk_g2s(sb + OFF_KVRAW, &g_kv[epoch & 1][sl * 2048], 8192, BAR(B_KVRAW));
            bulk_g2s(sb + OFF_KVRAW + 8192, &g_z[epoch & 1][sl * 128], 512, BAR(B_KVRAW));
          }
          mbar_wait(BAR(B_KVRAW), 0);
#pragma unroll 2
          for (int i = lane; i < 256; i += 32) {
            float4 v0 = lds128f(sb + OFF_KVRAW + i * 32), v1 = lds128f(sb + OFF_KVRAW + i * 32 + 16);
            int h = i >> 6, dd = (i >> 2) & 15, fo = i & 3;
            uint4 w; w.x = pack_bf16(v0.x, v0.y); w.y = pack_bf16(v0.z, v0.w); w.z = pack_bf16(v1.x, v1.y); w.w = pack_bf16(v1.z, v1.w);
            sts128(sb + OFF_KVB + h * 1536 + (fo >> 1) * 768 + (dd >> 3) * 256 + (fo & 1) * 128 + (dd & 7) * 16, w);
          }
          {
            const int h = lane >> 3, fo = (lane >> 1) & 3, half = lane & 1;
            float4 v0 = lds128f(sb + OFF_KVRAW + 8192 + h * 128 + fo * 32), v1 = lds128f(sb + OFF_KVRAW + 8192 + h * 128 + fo * 32 + 16);
            uint4 zz; zz.x = pack_bf16(v0.x, v0.y); zz.y = pack_bf16(v0.z, v0.w); zz.z = pack_bf16(v1.x, v1.y); zz.w = pack_bf16(v1.z, v1.w);
            uint32_t a = sb + OFF_KVB + h * 1536 + (fo >> 1) * 768 + 512 + (fo & 1) * 128 + half * 64;
            sts128(a, zz); sts128(a + 16, zz); sts128(a + 32, zz); sts128(a + 48, zz);
          }
          fence_async_smem();
          mbar_arrive(BAR(B_KVB));
          if (lane == 12) state = 2;
          MARK(3);
        }
        if (__all_sync(0xffffffffu, state == 2)) break;
        unsigned long long dl; asm volatile("ld.shared.u64 %0, [%1 + 1016];" : "=l"(dl) : "r"(bar0) : "memory");
        if (gtime() >= dl) break;
        __nanosleep(64);
      }
      MARK(2);
    }
    __syncwarp();
    teardown(false);
  } else {
    asm volatile("setmaxnreg.inc.sync.aligned.u32 232;");
    MARK(0);
    const int wg = warp >> 2, w4 = warp & 3;
    const int g = lane >> 2, t4 = lane & 3;
    const int tw = tid & 127;
    const uint32_t peer = (uint32_t)(kh ^ 1);
    {
      const int rsub = lane >> 3, sub = lane & 7;
      uint4 v[2][8];
      const int row0 = kh * 64 + warp * 8 + rsub;
      const __nv_bfloat16* xb = x + (size_t)(m * 128 + row0) * D_ + sub * 8;
#pragma unroll
      for (int gi = 0; gi < 2; gi++)
#pragma unroll
        for (int i = 0; i < 8; i++) v[gi][i] = ldg128(xb + gi * 4 * D_ + i * 64);
      asm volatile("barrier.cluster.wait.acquire.aligned;" ::: "memory");
      const uint32_t rbar = mapa(BAR(B_XNR), peer);
      const uint32_t rsb = mapa(sb, peer);
#pragma unroll
      for (int gi = 0; gi < 2; gi++) {
        float s = 0.f;
#pragma unroll
        for (int i = 0; i < 8; i++) {
          s += (bf_lo(v[gi][i].x) + bf_hi(v[gi][i].x)) + (bf_lo(v[gi][i].y) + bf_hi(v[gi][i].y));
          s += (bf_lo(v[gi][i].z) + bf_hi(v[gi][i].z)) + (bf_lo(v[gi][i].w) + bf_hi(v[gi][i].w));
        }
        s += __shfl_xor_sync(0xffffffffu, s, 1);
        s += __shfl_xor_sync(0xffffffffu, s, 2);
        s += __shfl_xor_sync(0xffffffffu, s, 4);
        if (gi == 0 && lane == 0) mbar_arrive(BAR(B_XLAND));
        MARK(16 + gi);
        const float mean = s * (1.f / 512.f);
        float q0 = 0.f, q1 = 0.f;
#pragma unroll
        for (int i = 0; i < 8; i++) {
          const uint32_t* w = reinterpret_cast<const uint32_t*>(&v[gi][i]);
#pragma unroll
          for (int e = 0; e < 4; e++) {
            float d0 = bf_lo(w[e]) - mean, d1 = bf_hi(w[e]) - mean;
            q0 = fmaf(d0, d0, q0); q1 = fmaf(d1, d1, q1);
          }
        }
        float q = q0 + q1;
        q += __shfl_xor_sync(0xffffffffu, q, 1);
        q += __shfl_xor_sync(0xffffffffu, q, 2);
        q += __shfl_xor_sync(0xffffffffu, q, 4);
        const float rstd = rsqrtf(q * (1.f / 512.f) + 1e-5f);
        const float nb = -mean * rstd;
        const int row = row0 + gi * 4;
        const uint32_t ro = OFF_XN + row * 128 + ((sub ^ (row & 7)) << 4);
#pragma unroll
        for (int i = 0; i < 8; i++) {
          const uint32_t* w = reinterpret_cast<const uint32_t*>(&v[gi][i]);
          uint4 o;
          o.x = pack_bf16(fmaf(bf_lo(w[0]), rstd, nb), fmaf(bf_hi(w[0]), rstd, nb));
          o.y = pack_bf16(fmaf(bf_lo(w[1]), rstd, nb), fmaf(bf_hi(w[1]), rstd, nb));
          o.z = pack_bf16(fmaf(bf_lo(w[2]), rstd, nb), fmaf(bf_hi(w[2]), rstd, nb));
          o.w = pack_bf16(fmaf(bf_lo(w[3]), rstd, nb), fmaf(bf_hi(w[3]), rstd, nb));
          st_async4u(rsb + ro + i * 16384, o, rbar);
          sts128(sb + ro + i * 16384, o);
        }
      }
      fence_async_smem();
      mbar_arrive(BAR(B_XNL));
      if (wg == kh) mbar_wait(BAR(B_XNL), 0);
      else { mbar_wait_cluster(BAR(B_XNR), 0); fence_async_smem(); }
    }
    MARK(1);
    const uint64_t dA0 = mkdesc(sb + OFF_XN + wg * 8192, 16, 1024, 1);
    const uint32_t st_off = (uint32_t)((2 * w4 + ((lane >> 3) & 1)) * 256 + (lane >> 4) * 128 + (lane & 7) * 16);

    uint32_t qp[16], kp[16], vp[16], phq[4][8];
    const uint64_t dWP = mkdesc(sb + OFF_WPHI, 128, 256, 0);
    {
      float a_qkv[96], a_gu[64];
#pragma unroll 1
      for (int j = 0; j < 16; j++) {
        mbar_wait(BAR(B_FULL1 + (j & 7)), (j >> 3) & 1);
        uint32_t bs = sb + OFF_Z + (uint32_t)((j + 2) & 3) * 20480u;
        uint64_t dB = mkdesc(bs, 4096, 1024, 1);
        uint64_t dA = dA0 + (uint64_t)(((j >> 1) * 16384 + (j & 1) * 64) >> 4);
        wg_fence();
        wgmma_n192(a_qkv, dA, dB, j > 0);
        wgmma_n128(a_gu, dA, dB + (12288 >> 4), j > 0);
        wgmma_n192(a_qkv, dA + 2, dB + (2048 >> 4), 1);
        wgmma_n128(a_gu, dA + 2, dB + ((12288 + 2048) >> 4), 1);
        wg_commit();
        if (j > 0) { wg_wait<1>(); if (lane == 0) mbar_arrive(BAR(B_EMPTY1 + ((j - 1) & 7))); }
      }
      wg_wait<0>();
      MARK(2);
      if (lane == 0) mbar_arrive(BAR(B_EMPTY1 + 7));
#pragma unroll
      for (int i = 0; i < 16; i++) {
        qp[i] = pack_bf16(a_qkv[2 * i], a_qkv[2 * i + 1]);
        kp[i] = pack_bf16(a_qkv[32 + 2 * i], a_qkv[32 + 2 * i + 1]);
        vp[i] = pack_bf16(a_qkv[64 + 2 * i], a_qkv[64 + 2 * i + 1]);
      }
      uint32_t rr[16];
#pragma unroll
      for (int e = 0; e < 16; e++)
        rr[e] = pack_bf16(silu_mul(a_gu[2 * e], a_gu[32 + 2 * e]), silu_mul(a_gu[2 * e + 1], a_gu[32 + 2 * e + 1]));
      mbar_wait(BAR(B_EMPTY1 + 6), 1);
      mbar_wait(BAR(B_EMPTY1 + 7), 1);
      const uint32_t hb = sb + OFF_H1 + wg * 8192 + st_off;
#pragma unroll
      for (int kb = 0; kb < 4; kb++) stsm4(hb + kb * 2048, rr[4 * kb], rr[4 * kb + 1], rr[4 * kb + 2], rr[4 * kb + 3]);
      fence_async_smem();
      mbar_arrive(BAR(B_H1 + wg));
    }
    MARK(3);
    {
      float ag[64], au[56];
      const uint32_t stg = sb + OFF_STG + wg * 12288;
      const uint32_t so = stg + (uint32_t)((2 * w4 + ((lane >> 3) & 1)) * 128 + (lane >> 4) * 1024 + (lane & 7) * 16);
      float keep[2][8], keepz[2][2];
      float dkv[16], dz[4], pa[8], pb[8];
      const uint64_t dPK = mkdesc(stg, 128, 1024, 0), dV = mkdesc(stg + 8192, 128, 1024, 0), dOne = mkdesc(sb + OFF_ONES, 0, 0, 0);
#pragma unroll
      for (int i = 0; i < 16; i++) {
        const int j = 16 + i;
        TRC(4 * i);
        mbar_wait(BAR(B_FULL1 + (j & 7)), (j >> 3) & 1);
        TRC(4 * i + 1);
        if (i == 0) mbar_wait(BAR(B_WPHI), 0);
        if (i == 3 || i == 6) named_bar(1 + wg, 128);
        uint64_t dG = mkdesc(sb + OFF_Z + 40960u + (uint32_t)((2 * i + 5) % 7) * 8192u, 4096, 1024, 1);
        uint64_t dU = mkdesc(sb + OFF_Z + 40960u + (uint32_t)((2 * i + 6) % 7) * 8192u, 4096, 1024, 1);
        uint64_t dA = dA0 + (uint64_t)(((i >> 1) * 16384 + (i & 1) * 64) >> 4);
        wg_fence();
        if (i == 0 || i == 3) {
          const int h = (i == 0) ? 0 : 2;
          wgmma_rs_n16(pa, kp[4 * h], kp[4 * h + 1], kp[4 * h + 2], kp[4 * h + 3], dWP + h * 32, 0);
          wgmma_rs_n16(pb, kp[4 * h + 4], kp[4 * h + 5], kp[4 * h + 6], kp[4 * h + 7], dWP + (h + 1) * 32, 0);
        }
        if (i == 6 || i == 10) {
          const int h = (i == 6) ? 0 : 2;
          wgmma_rs_n16(pa, qp[4 * h], qp[4 * h + 1], qp[4 * h + 2], qp[4 * h + 3], dWP + h * 32, 0);
          wgmma_rs_n16(pb, qp[4 * h + 4], qp[4 * h + 5], qp[4 * h + 6], qp[4 * h + 7], dWP + (h + 1) * 32, 0);
        }
        if (i == 3 || i == 6) {
#pragma unroll
          for (int ks = 0; ks < 4; ks++) {
            wgmma_n32_tt(dkv, dPK + ks * 16, dV + ks * 16, ks > 0);
            wgmma_n8_tt(dz, dPK + ks * 16, dOne, ks > 0);
          }
        }
        wgmma_n128(ag, dA, dG, i > 0);
        wgmma_n112(au, dA, dU, i > 0);
        wgmma_n128(ag, dA + 2, dG + 128, 1);
        wgmma_n112(au, dA + 2, dU + 128, 1);
        wg_commit();
        TRC(4 * i + 2);
        if (i > 0) {
          wg_wait<1>();
          TRC(4 * i + 3);
          if (lane == 0) {
            mbar_arrive(BAR(B_EMPTY1 + ((j - 1) & 7)));
            if (i == 10) mbar_arrive(BAR(B_XFREE));
          }
        }
        if (i == 4 || i == 7) {
          const int pr = (i == 4) ? 0 : 1;
#pragma unroll
          for (int e = 0; e < 8; e++) keep[pr][e] = (w4 >= 2) ? dkv[8 + e] : dkv[e];
          keepz[pr][0] = 0.5f * (dz[0] + dz[1]); keepz[pr][1] = 0.5f * (dz[2] + dz[3]);
          named_bar(1 + wg, 128);
        }
        if (i == 1 || i == 2 || i == 4 || i == 5) {
          const int h = (i < 3) ? i - 1 : i - 2, hh = h & 1;
          uint32_t ph[8];
          if (hh) hh_both(pb, ph); else hh_both(pa, ph);
          stsm4(so + hh * 4096, ph[0], ph[1], ph[2], ph[3]);
          stsm4(so + hh * 4096 + 2048, ph[4], ph[5], ph[6], ph[7]);
          stsm4(so + 8192 + hh * 2048, vp[4 * h], vp[4 * h + 1], vp[4 * h + 2], vp[4 * h + 3]);
          if (hh) fence_async_smem();
        }
        if (i == 7) {
#pragma unroll
          for (int p = 0; p < 2; p++) {
            const int h = p * 2 + (w4 >> 1), f = (w4 & 1) * 16 + g;
            uint32_t a = stg + h * 2048 + t4 * 256 + f * 4;
            sts32(a, __float_as_uint(keep[p][0]));              sts32(a + 128, __float_as_uint(keep[p][1]));
            sts32(a + 32, __float_as_uint(keep[p][2]));         sts32(a + 128 + 32, __float_as_uint(keep[p][3]));
            sts32(a + 1024, __float_as_uint(keep[p][4]));       sts32(a + 1024 + 128, __float_as_uint(keep[p][5]));
            sts32(a + 1024 + 32, __float_as_uint(keep[p][6]));  sts32(a + 1024 + 128 + 32, __float_as_uint(keep[p][7]));
            if (t4 == 0) {
              sts32(stg + 8192 + h * 128 + f * 4, __float_as_uint(keepz[p][0]));
              sts32(stg + 8192 + h * 128 + (f + 8) * 4, __float_as_uint(keepz[p][1]));
            }
          }
          fence_async_smem();
          mbar_arrive(BAR(B_KV + wg));
        }
        if (i == 8) hh_both(pa, phq[0]);
        if (i == 9) hh_both(pb, phq[1]);
        if (i == 11) hh_both(pa, phq[2]);
        if (i == 12) hh_both(pb, phq[3]);
      }
      wg_wait<0>();
      MARK(5);
      if (lane == 0) mbar_arrive(BAR(B_EMPTY1 + 7));
#pragma unroll
      for (int e = 56; e < 64; e++) KEEPF(ag[e]);
      named_bar(1 + wg, 128);
      const uint32_t hb = sb + OFF_XN + 5 * 16384 + wg * 8192 + st_off;
#pragma unroll
      for (int kb = 0; kb < 7; kb++) {
        uint32_t rr[4];
#pragma unroll
        for (int e = 0; e < 4; e++) {
          int idx = kb * 8 + e * 2;
          rr[e] = pack_bf16(silu_mul(ag[idx], au[idx]), silu_mul(ag[idx + 1], au[idx + 1]));
          if (kb == 6 && nq == 3) rr[e] = 0u;
        }
        stsm4(hb + (kb < 4 ? kb * 2048 : 16384 + (kb - 4) * 2048), rr[0], rr[1], rr[2], rr[3]);
      }
      fence_async_smem();
      mbar_arrive(BAR(B_H2 + wg));
      named_bar(1 + wg, 128);
    }
    MARK(6);
    {
      float a_o[64], a_s[64];
      const uint32_t own_ha = sb + OFF_H1 + wg * 8192;
      const uint32_t own_hb = sb + OFF_XN + 5 * 16384 + wg * 8192;
      const uint32_t own_hc = sb + OFF_XN + 6 * 16384 + wg * 8192;
      const uint32_t own_o  = sb + OFF_XN + 7 * 16384 + wg * 8192;
      {
        p2_step<-1, 0, 4, 1, -1, -1, 0>(a_o, sb, bar0, own_ha, lane);
        mbar_wait(BAR(B_KVB), 0);
        MARK(7);
        float nd[4][12];
        const uint64_t dKV = mkdesc(sb + OFF_KVB, 128, 256, 0);
        p2_issue<1, 2, 4, 0>(a_o, sb, bar0, wg * 8192);
#pragma unroll
        for (int h = 0; h < 4; h++) {
          wgmma_rs_n24(nd[h], phq[h][0], phq[h][1], phq[h][2], phq[h][3], dKV + h * 96, 0);
          wgmma_rs_n24(nd[h], phq[h][4], phq[h][5], phq[h][6], phq[h][7], dKV + h * 96 + 48, 1);
        }
        p2_commit<-1, 0, 1>(bar0, lane);
        p2_step<3, 4, 4, 0, 1, 2, 1>(a_o, sb, bar0, wg * 8192, lane);
#pragma unroll
        for (int h = 0; h < 4; h++) {
          float r0 = rcp(0.5f * (nd[h][8] + nd[h][9]) + 1e-6f), r1 = rcp(0.5f * (nd[h][10] + nd[h][11]) + 1e-6f);
          stsm4(own_o + st_off + h * 2048, pack_bf16(nd[h][0] * r0, nd[h][1] * r0), pack_bf16(nd[h][2] * r1, nd[h][3] * r1),
                pack_bf16(nd[h][4] * r0, nd[h][5] * r0), pack_bf16(nd[h][6] * r1, nd[h][7] * r1));
        }
        fence_async_smem();
        mbar_arrive(BAR(B_O + wg));
        p2_step<5, 6, 4, 0, 3, 4, 1>(a_o, sb, bar0, wg * 8192, lane);
        named_bar(1 + wg, 128);
      }
      MARK(9);
      p2_step<-1, 7, 4, 0, 5, -1, 1>(a_o, sb, bar0, own_hb, lane);
      p2_step<-1, 8, 3, 0, -1, 7, 1>(a_o, sb, bar0, own_hc, lane);
      p2_step<9, 10, 4, 0, -1, 8, 1>(a_o, sb, bar0, wg * 8192, lane);
      if (lane == 0) mbar_arrive_remote(mapa(BAR(B_XO_OK), peer));
      p2_step<11, 12, 3, 0, 9, 10, 1>(a_o, sb, bar0, wg * 6144, lane);
      p2_step<13, 14, 4, 0, 11, 12, 1>(a_o, sb, bar0, wg * 8192, lane);
      p2_step<15, 16, 3, 0, 13, 14, 1>(a_o, sb, bar0, wg * 6144, lane);
      p2_step<17, 18, 4, 0, -1, 16, 1>(a_o, sb, bar0, wg * 8192, lane);
      p2_step<19, 20, 3, 0, -1, 18, 1>(a_o, sb, bar0, wg * 6144, lane);
      if (lane == 0) mbar_arrive_remote(mapa(BAR(B_XS_OK), peer));
      uint32_t xr[16];
      {
        const uint32_t* xp = reinterpret_cast<const uint32_t*>(x + (size_t)(m * 128 + wg * 64 + w4 * 16 + g) * D_ + nq * 128 + kh * 64 + t4 * 2);
#pragma unroll
        for (int j = 0; j < 8; j++) { xr[2 * j] = __ldg(xp + j * 4); xr[2 * j + 1] = __ldg(xp + 8 * (D_ / 2) + j * 4); }
      }
      MARK(10);
      p2_step<-1, 21, 4, 1, 19, -1, 1>(a_s, sb, bar0, own_o, lane);
      {
        mbar_wait_cluster(BAR(B_XO_OK), 0);
        uint32_t ra = mapa(sb + OFF_XO_RECV + wg * 16384 + tw * 16, peer), rb = mapa(BAR(B_XO_FULL + wg), peer);
#pragma unroll
        for (int i = 0; i < 8; i++) st_async4(ra + i * 2048, a_o[32 + 4 * i], a_o[33 + 4 * i], a_o[34 + 4 * i], a_o[35 + 4 * i], rb);
      }
      p2_step<22, 23, 4, 0, -1, -1, 0>(a_s, sb, bar0, wg * 8192, lane);
      p2_step<24, 25, 4, 0, -1, -1, 0>(a_s, sb, bar0, wg * 8192, lane);
      mbar_wait_cluster(BAR(B_XO_FULL + wg), 0);
      float gt[32];
#pragma unroll
      for (int i = 0; i < 8; i++) {
        float4 v = lds128f(sb + OFF_XO_RECV + wg * 16384 + tw * 16 + i * 2048);
        float o0 = a_o[4 * i] + v.x, o1 = a_o[4 * i + 1] + v.y, o2 = a_o[4 * i + 2] + v.z, o3 = a_o[4 * i + 3] + v.w;
        gt[4 * i] = silu_mul(o0, 1.f); gt[4 * i + 1] = silu_mul(o1, 1.f); gt[4 * i + 2] = silu_mul(o2, 1.f); gt[4 * i + 3] = silu_mul(o3, 1.f);
      }
      p2_step<26, 27, 4, 0, -1, -1, 0>(a_s, sb, bar0, wg * 8192, lane);
      MARK(11);
      wg_wait<0>();
      MARK(12);
      {
        mbar_wait_cluster(BAR(B_XS_OK), 0);
        uint32_t ra = mapa(sb + OFF_XS_RECV + wg * 16384 + tw * 16, peer), rb = mapa(BAR(B_XS_FULL + wg), peer);
#pragma unroll
        for (int i = 0; i < 8; i++) st_async4(ra + i * 2048, a_s[32 + 4 * i], a_s[33 + 4 * i], a_s[34 + 4 * i], a_s[35 + 4 * i], rb);
      }
      MARK(13);
      mbar_wait_cluster(BAR(B_XS_FULL + wg), 0);
      MARK(14);
      uint32_t* op = reinterpret_cast<uint32_t*>(out + (size_t)(m * 128 + wg * 64 + w4 * 16 + g) * D_ + nq * 128 + kh * 64 + t4 * 2);
#pragma unroll
      for (int i = 0; i < 8; i++) {
        float4 v = lds128f(sb + OFF_XS_RECV + wg * 16384 + tw * 16 + i * 2048);
        float y0 = fmaf(a_s[4 * i] + v.x, gt[4 * i], bf_lo(xr[2 * i]));
        float y1 = fmaf(a_s[4 * i + 1] + v.y, gt[4 * i + 1], bf_hi(xr[2 * i]));
        float y2 = fmaf(a_s[4 * i + 2] + v.z, gt[4 * i + 2], bf_lo(xr[2 * i + 1]));
        float y3 = fmaf(a_s[4 * i + 3] + v.w, gt[4 * i + 3], bf_hi(xr[2 * i + 1]));
        op[i * 4] = pack_bf16(y0, y1);
        op[8 * (D_ / 2) + i * 4] = pack_bf16(y2, y3);
      }
    }
    MARK(15);
    teardown(tid == 0);
  }
}

typedef CUresult (*EncFn)(CUtensorMap*, CUtensorMapDataType, cuuint32_t, void*, const cuuint64_t*, const cuuint64_t*, const cuuint32_t*,
                          const cuuint32_t*, CUtensorMapInterleave, CUtensorMapSwizzle, CUtensorMapL2promotion, CUtensorMapFloatOOBfill);

void enc(EncFn fn, CUtensorMap* tm, const void* base, int rank, const cuuint64_t* gd, const cuuint64_t* gs, const cuuint32_t* bd) {
  cuuint32_t es[3] = {1, 1, 1};
  CUresult rc = fn(tm, CU_TENSOR_MAP_DATA_TYPE_BFLOAT16, (cuuint32_t)rank, const_cast<void*>(base), gd, gs, bd, es, CU_TENSOR_MAP_INTERLEAVE_NONE,
                   CU_TENSOR_MAP_SWIZZLE_128B, CU_TENSOR_MAP_L2_PROMOTION_L2_128B, CU_TENSOR_MAP_FLOAT_OOB_FILL_NONE);
  (void)rc;
}

}

extern "C" void kernel_launch(void* const* d_in, const int* in_sizes, int n_in, void* d_out, int out_size) {
  const __nv_bfloat16* x    = (const __nv_bfloat16*)d_in[0];
  const __nv_bfloat16* wqkv = (const __nv_bfloat16*)d_in[1];
  const __nv_bfloat16* wphi = (const __nv_bfloat16*)d_in[2];
  const __nv_bfloat16* wo   = (const __nv_bfloat16*)d_in[3];
  const __nv_bfloat16* w1   = (const __nv_bfloat16*)d_in[5];
  const __nv_bfloat16* w3   = (const __nv_bfloat16*)d_in[6];
  const __nv_bfloat16* w2   = (const __nv_bfloat16*)d_in[7];

  static EncFn fn = nullptr;
  if (!fn) {
    void* p = nullptr; cudaDriverEntryPointQueryResult qr;
    cudaGetDriverEntryPoint("cuTensorMapEncodeTiled", &p, cudaEnableDefault, &qr);
    fn = (EncFn)p;
    cudaFuncSetAttribute(fused_kernel, cudaFuncAttributeMaxDynamicSharedMemorySize, SMEM_BYTES);
  }
  TMaps tm;
  { cuuint64_t gd[3] = {512, 512, 3}; cuuint64_t gs[2] = {3072, 1024}; cuuint32_t bd[3] = {64, 32, 3};
    enc(fn, &tm.qkv, wqkv, 3, gd, gs, bd); }
  { cuuint64_t gd[2] = {F_, 512}; cuuint64_t gs[1] = {F_ * 2}; cuuint32_t bd[2] = {64, 32};
    enc(fn, &tm.w1, w1, 2, gd, gs, bd);  enc(fn, &tm.w3, w3, 2, gd, gs, bd);
  }
  { cuuint64_t gd[3] = {F_, 512, 2}; cuuint64_t gs[2] = {F_ * 2, 128}; cuuint32_t bd[3] = {64, 32, 2};
    enc(fn, &tm.w1p, w1, 3, gd, gs, bd); enc(fn, &tm.w3p, w3, 3, gd, gs, bd); }
  { cuuint64_t gd[2] = {512, F_}; cuuint64_t gs[1] = {1024}; cuuint32_t bd[2] = {64, 64}; cuuint32_t bd2[2] = {64, 48};
    enc(fn, &tm.w2, w2, 2, gd, gs, bd); enc(fn, &tm.w2t, w2, 2, gd, gs, bd2); }
  { cuuint64_t gd[2] = {512, 512}; cuuint64_t gs[1] = {1024}; cuuint32_t bd[2] = {64, 64};
    enc(fn, &tm.wo, wo, 2, gd, gs, bd); }

  cudaLaunchConfig_t cfg = {};
  cfg.gridDim = dim3(128); cfg.blockDim = dim3(384); cfg.dynamicSmemBytes = SMEM_BYTES; cfg.stream = cudaStreamPerThread;
  cudaLaunchKernelEx(&cfg, fused_kernel, tm, x, wphi, (__nv_bfloat16*)d_out);
}
```

```cpp
#include <cuda_runtime.h>
#include <cuda_bf16.h>
#include <cuda.h>
#include <stdint.h>

__device__ __forceinline__ void wgmma_n192(float (&d)[96], uint64_t da, uint64_t db, int scale_d) {
  asm volatile("{\n.reg .pred p;\nsetp.ne.b32 p, %98, 0;\n"
  "wgmma.mma_async.sync.aligned.m64n192k16.f32.bf16.bf16 {%0, %1, %2, %3, %4, %5, %6, %7, %8, %9, %10, %11, %12, %13, %14, %15, %16, %17, %18, %19, %20, %21, %22, %23, %24, %25, %26, %27, %28, %29, %30, %31, %32, %33, %34, %35, %36, %37, %38, %39, %40, %41, %42, %43, %44, %45, %46, %47, %48, %49, %50, %51, %52, %53, %54, %55, %56, %57, %58, %59, %60, %61, %62, %63, %64, %65, %66, %67, %68, %69, %70, %71, %72, %73, %74, %75, %76, %77, %78, %79, %80, %81, %82, %83, %84, %85, %86, %87, %88, %89, %90, %91, %92, %93, %94, %95}, %96, %97, p, 1, 1, 0, 1;\n}\n"
  : "+f"(d[0]), "+f"(d[1]), "+f"(d[2]), "+f"(d[3]), "+f"(d[4]), "+f"(d[5]), "+f"(d[6]), "+f"(d[7]), "+f"(d[8]), "+f"(d[9]), "+f"(d[10]), "+f"(d[11]), "+f"(d[12]), "+f"(d[13]), "+f"(d[14]), "+f"(d[15]), "+f"(d[16]), "+f"(d[17]), "+f"(d[18]), "+f"(d[19]), "+f"(d[20]), "+f"(d[21]), "+f"(d[22]), "+f"(d[23]), "+f"(d[24]), "+f"(d[25]), "+f"(d[26]), "+f"(d[27]), "+f"(d[28]), "+f"(d[29]), "+f"(d[30]), "+f"(d[31]), "+f"(d[32]), "+f"(d[33]), "+f"(d[34]), "+f"(d[35]), "+f"(d[36]), "+f"(d[37]), "+f"(d[38]), "+f"(d[39]), "+f"(d[40]), "+f"(d[41]), "+f"(d[42]), "+f"(d[43]), "+f"(d[44]), "+f"(d[45]), "+f"(d[46]), "+f"(d[47]), "+f"(d[48]), "+f"(d[49]), "+f"(d[50]), "+f"(d[51]), "+f"(d[52]), "+f"(d[53]), "+f"(d[54]), "+f"(d[55]), "+f"(d[56]), "+f"(d[57]), "+f"(d[58]), "+f"(d[59]), "+f"(d[60]), "+f"(d[61]), "+f"(d[62]), "+f"(d[63]), "+f"(d[64]), "+f"(d[65]), "+f"(d[66]), "+f"(d[67]), "+f"(d[68]), "+f"(d[69]), "+f"(d[70]), "+f"(d[71]), "+f"(d[72]), "+f"(d[73]), "+f"(d[74]), "+f"(d[75]), "+f"(d[76]), "+f"(d[77]), "+f"(d[78]), "+f"(d[79]), "+f"(d[80]), "+f"(d[81]), "+f"(d[82]), "+f"(d[83]), "+f"(d[84]), "+f"(d[85]), "+f"(d[86]), "+f"(d[87]), "+f"(d[88]), "+f"(d[89]), "+f"(d[90]), "+f"(d[91]), "+f"(d[92]), "+f"(d[93]), "+f"(d[94]), "+f"(d[95]) : "l"(da), "l"(db), "r"(scale_d));
}
__device__ __forceinline__ void wgmma_n128(float (&d)[64], uint64_t da, uint64_t db, int scale_d) {
  asm volatile("{\n.reg .pred p;\nsetp.ne.b32 p, %66, 0;\n"
  "wgmma.mma_async.sync.aligned.m64n128k16.f32.bf16.bf16 {%0, %1, %2, %3, %4, %5, %6, %7, %8, %9, %10, %11, %12, %13, %14, %15, %16, %17, %18, %19, %20, %21, %22, %23, %24, %25, %26, %27, %28, %29, %30, %31, %32, %33, %34, %35, %36, %37, %38, %39, %40, %41, %42, %43, %44, %45, %46, %47, %48, %49, %50, %51, %52, %53, %54, %55, %56, %57, %58, %59, %60, %61, %62, %63}, %64, %65, p, 1, 1, 0, 1;\n}\n"
  : "+f"(d[0]), "+f"(d[1]), "+f"(d[2]), "+f"(d[3]), "+f"(d[4]), "+f"(d[5]), "+f"(d[6]), "+f"(d[7]), "+f"(d[8]), "+f"(d[9]), "+f"(d[10]), "+f"(d[11]), "+f"(d[12]), "+f"(d[13]), "+f"(d[14]), "+f"(d[15]), "+f"(d[16]), "+f"(d[17]), "+f"(d[18]), "+f"(d[19]), "+f"(d[20]), "+f"(d[21]), "+f"(d[22]), "+f"(d[23]), "+f"(d[24]), "+f"(d[25]), "+f"(d[26]), "+f"(d[27]), "+f"(d[28]), "+f"(d[29]), "+f"(d[30]), "+f"(d[31]), "+f"(d[32]), "+f"(d[33]), "+f"(d[34]), "+f"(d[35]), "+f"(d[36]), "+f"(d[37]), "+f"(d[38]), "+f"(d[39]), "+f"(d[40]), "+f"(d[41]), "+f"(d[42]), "+f"(d[43]), "+f"(d[44]), "+f"(d[45]), "+f"(d[46]), "+f"(d[47]), "+f"(d[48]), "+f"(d[49]), "+f"(d[50]), "+f"(d[51]), "+f"(d[52]), "+f"(d[53]), "+f"(d[54]), "+f"(d[55]), "+f"(d[56]), "+f"(d[57]), "+f"(d[58]), "+f"(d[59]), "+f"(d[60]), "+f"(d[61]), "+f"(d[62]), "+f"(d[63]) : "l"(da), "l"(db), "r"(scale_d));
}
__device__ __forceinline__ void wgmma_n112(float (&d)[56], uint64_t da, uint64_t db, int scale_d) {
  asm volatile("{\n.reg .pred p;\nsetp.ne.b32 p, %58, 0;\n"
  "wgmma.mma_async.sync.aligned.m64n112k16.f32.bf16.bf16 {%0, %1, %2, %3, %4, %5, %6, %7, %8, %9, %10, %11, %12, %13, %14, %15, %16, %17, %18, %19, %20, %21, %22, %23, %24, %25, %26, %27, %28, %29, %30, %31, %32, %33, %34, %35, %36, %37, %38, %39, %40, %41, %42, %43, %44, %45, %46, %47, %48, %49, %50, %51, %52, %53, %54, %55}, %56, %57, p, 1, 1, 0, 1;\n}\n"
  : "+f"(d[0]), "+f"(d[1]), "+f"(d[2]), "+f"(d[3]), "+f"(d[4]), "+f"(d[5]), "+f"(d[6]), "+f"(d[7]), "+f"(d[8]), "+f"(d[9]), "+f"(d[10]), "+f"(d[11]), "+f"(d[12]), "+f"(d[13]), "+f"(d[14]), "+f"(d[15]), "+f"(d[16]), "+f"(d[17]), "+f"(d[18]), "+f"(d[19]), "+f"(d[20]), "+f"(d[21]), "+f"(d[22]), "+f"(d[23]), "+f"(d[24]), "+f"(d[25]), "+f"(d[26]), "+f"(d[27]), "+f"(d[28]), "+f"(d[29]), "+f"(d[30]), "+f"(d[31]), "+f"(d[32]), "+f"(d[33]), "+f"(d[34]), "+f"(d[35]), "+f"(d[36]), "+f"(d[37]), "+f"(d[38]), "+f"(d[39]), "+f"(d[40]), "+f"(d[41]), "+f"(d[42]), "+f"(d[43]), "+f"(d[44]), "+f"(d[45]), "+f"(d[46]), "+f"(d[47]), "+f"(d[48]), "+f"(d[49]), "+f"(d[50]), "+f"(d[51]), "+f"(d[52]), "+f"(d[53]), "+f"(d[54]), "+f"(d[55]) : "l"(da), "l"(db), "r"(scale_d));
}
__device__ __forceinline__ void wgmma_n32_tt(float (&d)[16], uint64_t da, uint64_t db, int scale_d) {
  asm volatile("{\n.reg .pred p;\nsetp.ne.b32 p, %18, 0;\n"
  "wgmma.mma_async.sync.aligned.m64n32k16.f32.bf16.bf16 {%0, %1, %2, %3, %4, %5, %6, %7, %8, %9, %10, %11, %12, %13, %14, %15}, %16, %17, p, 1, 1, 1, 1;\n}\n"
  : "+f"(d[0]), "+f"(d[1]), "+f"(d[2]), "+f"(d[3]), "+f"(d[4]), "+f"(d[5]), "+f"(d[6]), "+f"(d[7]), "+f"(d[8]), "+f"(d[9]), "+f"(d[10]), "+f"(d[11]), "+f"(d[12]), "+f"(d[13]), "+f"(d[14]), "+f"(d[15]) : "l"(da), "l"(db), "r"(scale_d));
}
__device__ __forceinline__ void wgmma_n8_tt(float (&d)[4], uint64_t da, uint64_t db, int scale_d) {
  asm volatile("{\n.reg .pred p;\nsetp.ne.b32 p, %6, 0;\n"
  "wgmma.mma_async.sync.aligned.m64n8k16.f32.bf16.bf16 {%0, %1, %2, %3}, %4, %5, p, 1, 1, 1, 1;\n}\n"
  : "+f"(d[0]), "+f"(d[1]), "+f"(d[2]), "+f"(d[3]) : "l"(da), "l"(db), "r"(scale_d));
}
__device__ __forceinline__ void wgmma_rs_n16(float (&d)[8], uint32_t a0, uint32_t a1, uint32_t a2, uint32_t a3, uint64_t db, int scale_d) {
  asm volatile("{\n.reg .pred p;\nsetp.ne.b32 p, %13, 0;\n"
  "wgmma.mma_async.sync.aligned.m64n16k16.f32.bf16.bf16 {%0, %1, %2, %3, %4, %5, %6, %7}, {%8, %9, %10, %11}, %12, p, 1, 1, 0;\n}\n"
  : "+f"(d[0]), "+f"(d[1]), "+f"(d[2]), "+f"(d[3]), "+f"(d[4]), "+f"(d[5]), "+f"(d[6]), "+f"(d[7]) : "r"(a0), "r"(a1), "r"(a2), "r"(a3), "l"(db), "r"(scale_d));
}
__device__ __forceinline__ void wgmma_rs_n24(float (&d)[12], uint32_t a0, uint32_t a1, uint32_t a2, uint32_t a3, uint64_t db, int scale_d) {
  asm volatile("{\n.reg .pred p;\nsetp.ne.b32 p, %17, 0;\n"
  "wgmma.mma_async.sync.aligned.m64n24k16.f32.bf16.bf16 {%0, %1, %2, %3, %4, %5, %6, %7, %8, %9, %10, %11}, {%12, %13, %14, %15}, %16, p, 1, 1, 0;\n}\n"
  : "+f"(d[0]), "+f"(d[1]), "+f"(d[2]), "+f"(d[3]), "+f"(d[4]), "+f"(d[5]), "+f"(d[6]), "+f"(d[7]), "+f"(d[8]), "+f"(d[9]), "+f"(d[10]), "+f"(d[11]) : "r"(a0), "r"(a1), "r"(a2), "r"(a3), "l"(db), "r"(scale_d));
}

namespace {

constexpr int S_ = 2048, D_ = 512, F_ = 1376;

constexpr uint32_t OFF_XN   = 0;
constexpr uint32_t OFF_Z    = 131072;
constexpr uint32_t OFF_H1   = OFF_Z;
constexpr uint32_t OFF_STG  = OFF_Z + 16384;
constexpr uint32_t OFF_KVB  = OFF_Z + 16384;
constexpr uint32_t OFF_MISC = OFF_Z + 98304;
constexpr uint32_t OFF_BAR  = OFF_MISC;
constexpr uint32_t OFF_ONES = OFF_MISC + 768;
constexpr uint32_t OFF_WPHI = OFF_MISC + 1024;
constexpr uint32_t SMEM_BYTES = OFF_MISC + 3072;

constexpr int B_FULL1 = 0, B_EMPTY1 = 8;
constexpr int B_FULLT = 16;
constexpr int B_EMPTYT = 44;
constexpr int B_H1 = 67, B_KV = 69, B_H2 = 71, B_O = 73;
constexpr int B_KVDONE = 75, B_KVB = 76, B_XO_OK = 77, B_XS_OK = 78, B_XO_FULL = 79, B_XS_FULL = 81;
constexpr int B_WPHI = 83, B_XNL = 84, B_XNR = 85, B_XLAND = 86, B_XFREE = 87, B_KVRAW = 88, B_H2RD = 89;
constexpr int NBAR = 90;
constexpr uint32_t OFF_KVRAW = OFF_Z + 24576;

__host__ __device__ constexpr uint32_t slot2_off(int s) {
  return s < 7 ? (uint32_t)s * 16384u : (s < 11 ? OFF_Z + 24576u + (uint32_t)(s - 7) * 16384u : OFF_H1);
}
constexpr uint32_t OFF_XS_RECV = OFF_Z + 24576;
constexpr uint32_t OFF_XO_RECV = OFF_Z + 57344;
__host__ __device__ constexpr int tile_slot(int t) {
  constexpr int tb[28] = {0, 1, 2, 3, 4, 7, 10, 8, 9, 11, 0, 1, 2, 3, 4, 7, 5, 8, 6, 11, 0, 1, 2, 3, 4, 5, 6, 11};
  return tb[t];
}
__host__ __device__ constexpr int tile_prev(int t) {
  constexpr int tb[28] = {-1, -1, -1, -1, -1, -1, -1, -1, -1, 0, 0, 1, 2, 3, 4, 5, 7, 7, 8, 9, 10, 11, 12, 13, 14, 16, 18, 19};
  return tb[t];
}
__device__ __constant__ signed char c_tile_slot[28] = {0, 1, 2, 3, 4, 7, 10, 8, 9, 11, 0, 1, 2, 3, 4, 7, 5, 8, 6, 11, 0, 1, 2, 3, 4, 5, 6, 11};
__device__ __constant__ signed char c_tile_prev[28] = {-1, -1, -1, -1, -1, -1, -1, -1, -1, 0, 0, 1, 2, 3, 4, 5, 7, 7, 8, 9, 10, 11, 12, 13, 14, 16, 18, 19};

__device__ __constant__ signed char c_btile[16] = {0, 2, 4, 6, 8, 7, 10, 12, 14, 16, 18, 20, 21, 23, 25, 27};
__device__ __constant__ signed char c_bkind[16] = {0, 4, 8, 12, 2, 1, 5, 6, 9, 10, 13, 14, 3, 7, 11, 15};

__device__ __align__(1024) unsigned char g_ha[16 * 8 * 16384];
__device__ __align__(1024) unsigned char g_hb[16 * 8 * 16384];
__device__ __align__(1024) unsigned char g_hc[16 * 8 * 12288];
__device__ __align__(1024) unsigned char g_o [16 * 8 * 16384];
__device__ __align__(1024) float g_kv[2][32 * 512];
__device__ __align__(1024) float g_z [2][32 * 32];
__device__ unsigned int g_flag_ha[128 * 8];
__device__ unsigned int g_flag_hb[128 * 8];
__device__ unsigned int g_flag_o [128 * 8];
__device__ unsigned int g_kvcnt[8 * 8];
__device__ unsigned int g_epoch;
__device__ unsigned int g_done;

#define MARK(i)
#define TRC(i)
#define TRP(i)

struct TMaps {
  CUtensorMap qkv, w1, w3, w1p, w3p, w2, w2t, wo;
};

__device__ __forceinline__ uint32_t smem_u32(const void* p) { return (uint32_t)__cvta_generic_to_shared(p); }
__device__ __forceinline__ void mbar_init(uint32_t bar, int cnt) { asm volatile("mbarrier.init.shared::cta.b64 [%0], %1;" ::"r"(bar), "r"(cnt)); }
__device__ __forceinline__ void mbar_expect_tx(uint32_t bar, uint32_t bytes) { asm volatile("mbarrier.arrive.expect_tx.shared::cta.b64 _, [%0], %1;" ::"r"(bar), "r"(bytes) : "memory"); }
__device__ __forceinline__ void mbar_arrive(uint32_t bar) { asm volatile("mbarrier.arrive.shared::cta.b64 _, [%0];" ::"r"(bar) : "memory"); }
__device__ __forceinline__ void mbar_wait(uint32_t bar, uint32_t parity) {
  asm volatile("{\n.reg .pred p;\n.reg .u64 t, d;\n.reg .u32 a;\n"
               "WAIT_LOOP:\nmbarrier.try_wait.parity.shared::cta.b64 p, [%0], %1;\n@p bra WAIT_DONE;\n"
               "and.b32 a, %0, 0xFFFFFC00;\nld.shared.u64 d, [a + 1016];\nmov.u64 t, %%globaltimer;\nsetp.lt.u64 p, t, d;\n@p bra WAIT_LOOP;\nWAIT_DONE:\n}\n" ::"r"(bar), "r"(parity) : "memory");
}
__device__ __forceinline__ void mbar_wait_cluster(uint32_t bar, uint32_t parity) {
  asm volatile("{\n.reg .pred p;\n.reg .u64 t, d;\n.reg .u32 a;\n"
               "WAIT_LOOP:\nmbarrier.try_wait.parity.acquire.cluster.shared::cta.b64 p, [%0], %1;\n@p bra WAIT_DONE;\n"
               "and.b32 a, %0, 0xFFFFFC00;\nld.shared.u64 d, [a + 1016];\nmov.u64 t, %%globaltimer;\nsetp.lt.u64 p, t, d;\n@p bra WAIT_LOOP;\nWAIT_DONE:\n}\n" ::"r"(bar), "r"(parity) : "memory");
}
__device__ __forceinline__ unsigned long long gtime() { unsigned long long t; asm volatile("mov.u64 %0, %%globaltimer;" : "=l"(t)); return t; }
__device__ __forceinline__ uint32_t mapa(uint32_t addr, uint32_t cta) { uint32_t r; asm volatile("mapa.shared::cluster.u32 %0, %1, %2;" : "=r"(r) : "r"(addr), "r"(cta)); return r; }
__device__ __forceinline__ void mbar_arrive_remote(uint32_t raddr) { asm volatile("mbarrier.arrive.shared::cluster.b64 _, [%0];" ::"r"(raddr) : "memory"); }
__device__ __forceinline__ void tma2d(uint32_t dst, const CUtensorMap* tm, int c0, int c1, uint32_t bar) {
  asm volatile("cp.async.bulk.tensor.2d.shared::cluster.global.mbarrier::complete_tx::bytes [%0], [%1, {%3, %4}], [%2];" ::"r"(dst), "l"(tm), "r"(bar), "r"(c0), "r"(c1) : "memory");
}
__device__ __forceinline__ void tma3d(uint32_t dst, const CUtensorMap* tm, int c0, int c1, int c2, uint32_t bar) {
  asm volatile("cp.async.bulk.tensor.3d.shared::cluster.global.mbarrier::complete_tx::bytes [%0], [%1, {%3, %4, %5}], [%2];" ::"r"(dst), "l"(tm), "r"(bar), "r"(c0), "r"(c1), "r"(c2) : "memory");
}
__device__ __forceinline__ void pf2d(const CUtensorMap* tm, int c0, int c1) {
  asm volatile("cp.async.bulk.prefetch.tensor.2d.L2.global [%0, {%1, %2}];" ::"l"(tm), "r"(c0), "r"(c1) : "memory");
}
__device__ __forceinline__ void pf3d(const CUtensorMap* tm, int c0, int c1, int c2) {
  asm volatile("cp.async.bulk.prefetch.tensor.3d.L2.global [%0, {%1, %2, %3}];" ::"l"(tm), "r"(c0), "r"(c1), "r"(c2) : "memory");
}
__device__ __forceinline__ void bulk_g2s(uint32_t dst, const void* src, uint32_t bytes, uint32_t bar) {
  asm volatile("cp.async.bulk.shared::cluster.global.mbarrier::complete_tx::bytes [%0], [%1], %2, [%3];" ::"r"(dst), "l"(src), "r"(bytes), "r"(bar) : "memory");
}
__device__ __forceinline__ void bulk_s2g(void* dst, uint32_t src, uint32_t bytes) {
  asm volatile("cp.async.bulk.global.shared::cta.bulk_group [%0], [%1], %2;" ::"l"(dst), "r"(src), "r"(bytes) : "memory");
}
__device__ __forceinline__ void bulk_red_add_f32(void* dst, uint32_t src, uint32_t bytes) {
  asm volatile("cp.reduce.async.bulk.global.shared::cta.bulk_group.add.f32 [%0], [%1], %2;" ::"l"(dst), "r"(src), "r"(bytes) : "memory");
}
__device__ __forceinline__ void bulk_commit() { asm volatile("cp.async.bulk.commit_group;" ::: "memory"); }
__device__ __forceinline__ void bulk_wait0() { asm volatile("cp.async.bulk.wait_group 0;" ::: "memory"); }
__device__ __forceinline__ void fence_async_smem() { asm volatile("fence.proxy.async.shared::cta;" ::: "memory"); }
__device__ __forceinline__ void fence_async_all() { asm volatile("fence.proxy.async;" ::: "memory"); }
__device__ __forceinline__ void red_release_gpu(unsigned int* p, unsigned int v) { asm volatile("red.release.gpu.global.add.u32 [%0], %1;" ::"l"(p), "r"(v) : "memory"); }
__device__ __forceinline__ unsigned int ld_acquire_gpu(const unsigned int* p) { unsigned int v; asm volatile("ld.acquire.gpu.global.u32 %0, [%1];" : "=r"(v) : "l"(p) : "memory"); return v; }
__device__ __forceinline__ void wait_flag(const unsigned int* p, unsigned int target, uint32_t bar0) {
  while ((int)(ld_acquire_gpu(p) - target) < 0) {
    unsigned long long d; asm volatile("ld.shared.u64 %0, [%1 + 1016];" : "=l"(d) : "r"(bar0) : "memory");
    if (gtime() >= d) break;
  }
}
__device__ __forceinline__ void wg_fence() { asm volatile("wgmma.fence.sync.aligned;" ::: "memory"); }
__device__ __forceinline__ void wg_commit() { asm volatile("wgmma.commit_group.sync.aligned;" ::: "memory"); }
template <int N> __device__ __forceinline__ void wg_wait() { asm volatile("wgmma.wait_group.sync.aligned %0;" ::"n"(N) : "memory"); }
__device__ __forceinline__ void named_bar(int id, int n) { asm volatile("bar.sync %0, %1;" ::"r"(id), "r"(n) : "memory"); }
__device__ __forceinline__ uint64_t mkdesc(uint32_t addr, uint32_t lbo, uint32_t sbo, uint32_t mode) {
  return (uint64_t)((addr & 0x3FFFF) >> 4) | ((uint64_t)(lbo >> 4) << 16) | ((uint64_t)(sbo >> 4) << 32) | ((uint64_t)mode << 62);
}
__device__ __forceinline__ uint32_t pack_bf16(float lo, float hi) { uint32_t r; asm("cvt.rn.bf16x2.f32 %0, %1, %2;" : "=r"(r) : "f"(hi), "f"(lo)); return r; }
__device__ __forceinline__ float bf_lo(uint32_t v) { return __uint_as_float(v << 16); }
__device__ __forceinline__ float bf_hi(uint32_t v) { return __uint_as_float(v & 0xFFFF0000u); }
__device__ __forceinline__ float ex2(float x) { float r; asm("ex2.approx.ftz.f32 %0, %1;" : "=f"(r) : "f"(x)); return r; }
__device__ __forceinline__ float rcp(float x) { float r; asm("rcp.approx.ftz.f32 %0, %1;" : "=f"(r) : "f"(x)); return r; }
__device__ __forceinline__ float tanh_a(float x) { float r; asm("tanh.approx.f32 %0, %1;" : "=f"(r) : "f"(x)); return r; }
__device__ __forceinline__ float silu_mul(float g, float u) { float hg = 0.5f * g; float a = hg * u; return fmaf(a, tanh_a(hg), a); }
__device__ __forceinline__ void stsm4(uint32_t addr, uint32_t r0, uint32_t r1, uint32_t r2, uint32_t r3) {
  asm volatile("stmatrix.sync.aligned.m8n8.x4.shared.b16 [%0], {%1, %2, %3, %4};" ::"r"(addr), "r"(r0), "r"(r1), "r"(r2), "r"(r3) : "memory");
}
__device__ __forceinline__ void mma16816(float (&c)[4], uint32_t a0, uint32_t a1, uint32_t a2, uint32_t a3, uint32_t b0, uint32_t b1) {
  asm volatile("mma.sync.aligned.m16n8k16.row.col.f32.bf16.bf16.f32 {%0,%1,%2,%3}, {%4,%5,%6,%7}, {%8,%9}, {%0,%1,%2,%3};"
               : "+f"(c[0]), "+f"(c[1]), "+f"(c[2]), "+f"(c[3]) : "r"(a0), "r"(a1), "r"(a2), "r"(a3), "r"(b0), "r"(b1));
}
__device__ __forceinline__ uint32_t lds32(uint32_t a) { uint32_t v; asm volatile("ld.shared.u32 %0, [%1];" : "=r"(v) : "r"(a) : "memory"); return v; }
__device__ __forceinline__ void sts32(uint32_t a, uint32_t v) { asm volatile("st.shared.u32 [%0], %1;" ::"r"(a), "r"(v) : "memory"); }
__device__ __forceinline__ void sts16(uint32_t a, unsigned short v) { asm volatile("st.shared.u16 [%0], %1;" ::"r"(a), "h"(v) : "memory"); }
__device__ __forceinline__ void sts64f(uint32_t a, float x, float y) { asm volatile("st.shared.v2.f32 [%0], {%1, %2};" ::"r"(a), "f"(x), "f"(y) : "memory"); }
__device__ __forceinline__ void sts128(uint32_t a, uint4 v) { asm volatile("st.shared.v4.u32 [%0], {%1,%2,%3,%4};" ::"r"(a), "r"(v.x), "r"(v.y), "r"(v.z), "r"(v.w) : "memory"); }
__device__ __forceinline__ float4 lds128f(uint32_t a) { float4 v; asm volatile("ld.shared.v4.f32 {%0,%1,%2,%3}, [%4];" : "=f"(v.x), "=f"(v.y), "=f"(v.z), "=f"(v.w) : "r"(a) : "memory"); return v; }
__device__ __forceinline__ void st_async4(uint32_t raddr, float a, float b, float c, float d, uint32_t rbar) {
  asm volatile("st.async.weak.shared::cluster.mbarrier::complete_tx::bytes.v4.f32 [%0], {%1,%2,%3,%4}, [%5];" ::"r"(raddr), "f"(a), "f"(b), "f"(c), "f"(d), "r"(rbar) : "memory");
}
__device__ __forceinline__ uint4 ldg128(const void* p) { uint4 v; asm volatile("ld.global.nc.L1::no_allocate.v4.u32 {%0,%1,%2,%3}, [%4];" : "=r"(v.x), "=r"(v.y), "=r"(v.z), "=r"(v.w) : "l"(p)); return v; }

constexpr float LOG2E = 1.4426950408889634f;

__device__ __forceinline__ uint32_t mbar_test(uint32_t bar, uint32_t parity) {
  uint32_t ok;
  asm volatile("{\n.reg .pred p;\nmbarrier.test_wait.parity.shared::cta.b64 p, [%1], %2;\nselp.u32 %0, 1, 0, p;\n}\n" : "=r"(ok) : "r"(bar), "r"(parity) : "memory");
  return ok;
}
__device__ __forceinline__ void st_async4u(uint32_t raddr, uint4 v, uint32_t rbar) {
  asm volatile("st.async.weak.shared::cluster.mbarrier::complete_tx::bytes.v4.b32 [%0], {%1,%2,%3,%4}, [%5];" ::"r"(raddr), "r"(v.x), "r"(v.y), "r"(v.z), "r"(v.w), "r"(rbar) : "memory");
}
#define KEEPF(x) asm volatile("" ::"f"(x))

__device__ __forceinline__ void hh_both(const float (&p)[8], uint32_t (&ph)[8]) {
  const float* p0 = p; const float* p1 = p + 4;
  float mx[2], mn[2];
#pragma unroll
  for (int i = 0; i < 2; i++) {
    mx[i] = fmaxf(fmaxf(p0[2 * i], p0[2 * i + 1]), fmaxf(p1[2 * i], p1[2 * i + 1]));
    mn[i] = fminf(fminf(p0[2 * i], p0[2 * i + 1]), fminf(p1[2 * i], p1[2 * i + 1]));
  }
#pragma unroll
  for (int o = 1; o <= 2; o <<= 1) {
#pragma unroll
    for (int i = 0; i < 2; i++) {
      mx[i] = fmaxf(mx[i], __shfl_xor_sync(0xffffffffu, mx[i], o));
      mn[i] = fminf(mn[i], __shfl_xor_sync(0xffffffffu, mn[i], o));
    }
  }
  float e[2][4], f[2][4], sp[2], sn[2];
#pragma unroll
  for (int i = 0; i < 2; i++) {
    float mxl = -mx[i] * LOG2E, mnl = mn[i] * LOG2E;
    float v[4] = {p0[2 * i], p0[2 * i + 1], p1[2 * i], p1[2 * i + 1]};
#pragma unroll
    for (int c = 0; c < 4; c++) { e[i][c] = ex2(fmaf(v[c], LOG2E, mxl)); f[i][c] = ex2(fmaf(v[c], -LOG2E, mnl)); }
    sp[i] = (e[i][0] + e[i][1]) + (e[i][2] + e[i][3]);
    sn[i] = (f[i][0] + f[i][1]) + (f[i][2] + f[i][3]);
  }
#pragma unroll
  for (int o = 1; o <= 2; o <<= 1) {
#pragma unroll
    for (int i = 0; i < 2; i++) {
      sp[i] += __shfl_xor_sync(0xffffffffu, sp[i], o);
      sn[i] += __shfl_xor_sync(0xffffffffu, sn[i], o);
    }
  }
#pragma unroll
  for (int i = 0; i < 2; i++) {
    float rp = rcp(sp[i]), rn = rcp(sn[i]);
    ph[0 + i] = pack_bf16(e[i][0] * rp, e[i][1] * rp);
    ph[2 + i] = pack_bf16(e[i][2] * rp, e[i][3] * rp);
    ph[4 + i] = pack_bf16(f[i][0] * rn, f[i][1] * rn);
    ph[6 + i] = pack_bf16(f[i][2] * rn, f[i][3] * rn);
  }
}

template <int TA, int TB, int NK, int FIRST>
__device__ __forceinline__ void p2_issue(float (&acc)[64], uint32_t sb, uint32_t bar0, uint32_t aoff) {
  uint32_t aaddr = aoff;
  if (TA >= 0) {
    mbar_wait(bar0 + 8u * (B_FULLT + (TA < 0 ? 0 : TA)), 0);
    aaddr = sb + slot2_off(tile_slot(TA < 0 ? 0 : TA)) + aoff;
  }
  mbar_wait(bar0 + 8u * (B_FULLT + TB), 0);
  uint64_t dA = mkdesc(aaddr, 128, 256, 0), dB = mkdesc(sb + slot2_off(tile_slot(TB)), 8192, 1024, 1);
  wg_fence();
  wgmma_n128(acc, dA, dB, FIRST ? 0 : 1);
  wgmma_n128(acc, dA + 128, dB + 128, 1);
  wgmma_n128(acc, dA + 256, dB + 256, 1);
  if (NK > 3) wgmma_n128(acc, dA + 384, dB + 384, 1);
}
template <int RA, int RB, int WAITPREV>
__device__ __forceinline__ void p2_commit(uint32_t bar0, int lane) {
  wg_commit();
  if (WAITPREV) {
    wg_wait<1>();
    if (lane == 0) {
      if (RA >= 0) mbar_arrive(bar0 + 8u * (B_EMPTYT + (RA < 0 ? 0 : RA)));
      if (RB >= 0) mbar_arrive(bar0 + 8u * (B_EMPTYT + (RB < 0 ? 0 : RB)));
    }
  }
}
template <int TA, int TB, int NK, int FIRST, int RA, int RB, int WAITPREV>
__device__ __forceinline__ void p2_step(float (&acc)[64], uint32_t sb, uint32_t bar0, uint32_t aoff, int lane) {
  p2_issue<TA, TB, NK, FIRST>(acc, sb, bar0, aoff);
  p2_commit<RA, RB, WAITPREV>(bar0, lane);
}

__device__ __forceinline__ void pass2(const int wg, float (&ag)[64], float (&au)[56], const uint32_t (&qp)[16], const uint32_t (&kp)[16], const uint32_t (&vp)[16],
                                      uint32_t (&phq)[4][8], uint32_t sb, uint32_t bar0, uint64_t dA0, uint64_t dWP, int lane, int w4, int bid) {
  constexpr int WG = 0;
  auto BAR = [&](int i) { return bar0 + 8u * (uint32_t)i; };
  const int g = lane >> 2, t4 = lane & 3;
  const uint32_t stg = sb + OFF_STG + wg * 12288;
  const uint32_t so = stg + (uint32_t)((2 * w4 + ((lane >> 3) & 1)) * 128 + (lane >> 4) * 1024 + (lane & 7) * 16);
  float keep[2][8], keepz[2][2];
  float dkv[16], dz[4], pa[8], pb[8];
  const uint64_t dPK = mkdesc(stg, 128, 1024, 0), dV = mkdesc(stg + 8192, 128, 1024, 0), dOne = mkdesc(sb + OFF_ONES, 0, 0, 0);
#pragma unroll
  for (int i = 0; i < 16; i++) {
    const int j = 16 + i, c = i - WG;
    TRC(4 * i);
    mbar_wait(BAR(B_FULL1 + (j & 7)), (j >> 3) & 1);
    TRC(4 * i + 1);
    if (c == 0) mbar_wait(BAR(B_WPHI), 0);
    if (c == 4 || c == 8) named_bar(1 + wg, 128);
    uint64_t dG = mkdesc(sb + OFF_Z + 40960u + (uint32_t)((2 * i + 5) % 7) * 8192u, 4096, 1024, 1);
    uint64_t dU = mkdesc(sb + OFF_Z + 40960u + (uint32_t)((2 * i + 6) % 7) * 8192u, 4096, 1024, 1);
    uint64_t dA = dA0 + (uint64_t)(((i >> 1) * 16384 + (i & 1) * 64) >> 4);
    wg_fence();
    if (c == 0 || c == 4) {
      const int h = (c == 0) ? 0 : 2;
      wgmma_rs_n16(pa, kp[4 * h], kp[4 * h + 1], kp[4 * h + 2], kp[4 * h + 3], dWP + h * 32, 0);
      wgmma_rs_n16(pb, kp[4 * h + 4], kp[4 * h + 5], kp[4 * h + 6], kp[4 * h + 7], dWP + (h + 1) * 32, 0);
    }
    if (c == 8 || c == 12) {
      const int h = (c == 8) ? 0 : 2;
      wgmma_rs_n16(pa, qp[4 * h], qp[4 * h + 1], qp[4 * h + 2], qp[4 * h + 3], dWP + h * 32, 0);
      wgmma_rs_n16(pb, qp[4 * h + 4], qp[4 * h + 5], qp[4 * h + 6], qp[4 * h + 7], dWP + (h + 1) * 32, 0);
    }
    if (c == 4 || c == 8) {
#pragma unroll
      for (int ks = 0; ks < 4; ks++) {
        wgmma_n32_tt(dkv, dPK + ks * 16, dV + ks * 16, ks > 0);
        wgmma_n8_tt(dz, dPK + ks * 16, dOne, ks > 0);
      }
    }
    wgmma_n128(ag, dA, dG, i > 0);
    wgmma_n112(au, dA, dU, i > 0);
    wgmma_n128(ag, dA + 2, dG + 128, 1);
    wgmma_n112(au, dA + 2, dU + 128, 1);
    wg_commit();
    TRC(4 * i + 2);
    if (i > 0) {
      wg_wait<1>();
      TRC(4 * i + 3);
      if (lane == 0) {
        mbar_arrive(BAR(B_EMPTY1 + ((j - 1) & 7)));
        if (i == 10) mbar_arrive(BAR(B_XFREE));
      }
    }
    if (c == 5 || c == 9) {
      const int pr = (c == 5) ? 0 : 1;
#pragma unroll
      for (int e = 0; e < 8; e++) keep[pr][e] = (w4 >= 2) ? dkv[8 + e] : dkv[e];
      keepz[pr][0] = 0.5f * (dz[0] + dz[1]); keepz[pr][1] = 0.5f * (dz[2] + dz[3]);
      named_bar(1 + wg, 128);
    }
    if (c == 9) {
#pragma unroll
      for (int p = 0; p < 2; p++) {
        const int h = p * 2 + (w4 >> 1), f = (w4 & 1) * 16 + g;
        uint32_t a = stg + h * 2048 + t4 * 256 + f * 4;
        sts32(a, __float_as_uint(keep[p][0]));              sts32(a + 128, __float_as_uint(keep[p][1]));
        sts32(a + 32, __float_as_uint(keep[p][2]));         sts32(a + 128 + 32, __float_as_uint(keep[p][3]));
        sts32(a + 1024, __float_as_uint(keep[p][4]));       sts32(a + 1024 + 128, __float_as_uint(keep[p][5]));
        sts32(a + 1024 + 32, __float_as_uint(keep[p][6]));  sts32(a + 1024 + 128 + 32, __float_as_uint(keep[p][7]));
        if (t4 == 0) {
          sts32(stg + 8192 + h * 128 + f * 4, __float_as_uint(keepz[p][0]));
          sts32(stg + 8192 + h * 128 + (f + 8) * 4, __float_as_uint(keepz[p][1]));
        }
      }
      fence_async_smem();
      mbar_arrive(BAR(B_KV + wg));
    }
    if (c == 1 || c == 3 || c == 5 || c == 7) {
      const int h = (c - 1) >> 1, hh = h & 1;
      uint32_t ph[8];
      if (hh) hh_both(pb, ph); else hh_both(pa, ph);
      stsm4(so + hh * 4096, ph[0], ph[1], ph[2], ph[3]);
      stsm4(so + hh * 4096 + 2048, ph[4], ph[5], ph[6], ph[7]);
      stsm4(so + 8192 + hh * 2048, vp[4 * h], vp[4 * h + 1], vp[4 * h + 2], vp[4 * h + 3]);
      if (hh) fence_async_smem();
    }
    if (c == 9) hh_both(pa, phq[0]);
    if (c == 11) hh_both(pb, phq[1]);
    if (c == 13) hh_both(pa, phq[2]);
    if (c == 15) hh_both(pb, phq[3]);
  }
  if (WG == 1) hh_both(pb, phq[3]);
}

__device__ __forceinline__ void teardown(bool leader) {
  if (leader) {
    unsigned int tk = atomicAdd(&g_done, 1u);
    if ((tk & 127u) == 127u) { atomicAdd(&g_epoch, 1u); }
  }
}

__global__ void __cluster_dims__(2, 1, 1) __launch_bounds__(384, 1)
fused_kernel(const __grid_constant__ TMaps tm, const __nv_bfloat16* __restrict__ x, const __nv_bfloat16* __restrict__ wphi,
             __nv_bfloat16* __restrict__ out) {
  extern __shared__ __align__(1024) unsigned char smem_raw[];
  const uint32_t sb = smem_u32(smem_raw);
  const int tid = threadIdx.x;
  const int warp = tid >> 5, lane = tid & 31;
  const int bid = blockIdx.x;
  const int m = bid >> 3, r = bid & 7, nq = r >> 1, kh = r & 1;
  const int sl = kh * 4 + nq;
  const int f0 = kh * 688 + nq * 176;
  const uint32_t bar0 = sb + OFF_BAR;
  auto BAR = [&](int i) { return bar0 + 8u * (uint32_t)i; };

  if (tid == 128) asm volatile("st.shared.u64 [%0 + 1016], %1;" ::"r"(bar0), "l"(gtime() + 2000000ull) : "memory");
  if (tid < NBAR) {
    int cnt = 1;
    if (tid >= B_EMPTY1 && tid < B_EMPTY1 + 8) cnt = 8;
    else if (tid >= B_EMPTYT && tid < B_EMPTYT + 23) cnt = 8;
    else if (tid >= B_H1 && tid < B_KVDONE) cnt = 128;
    else if (tid == B_KVDONE || tid == B_H2RD) cnt = 2;
    else if (tid == B_KVB || tid == B_WPHI) cnt = 32;
    else if (tid == B_XO_OK || tid == B_XS_OK || tid == B_XLAND || tid == B_XFREE) cnt = 8;
    else if (tid == B_XNL) cnt = 256;
    mbar_init(BAR(tid), cnt);
    if (tid == B_XNR) mbar_expect_tx(BAR(B_XNR), 65536);
    if (tid >= B_XO_FULL && tid < B_XO_FULL + 4) mbar_expect_tx(BAR(tid), 16384);
    asm volatile("fence.mbarrier_init.release.cluster;" ::: "memory");
  }
  __syncthreads();
  asm volatile("barrier.cluster.arrive.relaxed.aligned;" ::: "memory");

  if (warp >= 8) {
    asm volatile("setmaxnreg.dec.sync.aligned.u32 40;");
    asm volatile("barrier.cluster.wait.aligned;" ::: "memory");
    if (warp == 8) {
      if (lane == 0) {
        MARK(0);
        mbar_wait(BAR(B_XLAND), 0);
#pragma unroll 1
        for (int j = 0; j < 16; j++) {
          if (j >= 4) mbar_wait(BAR(B_EMPTY1 + ((j - 4) & 7)), ((j - 4) >> 3) & 1);
          uint32_t dst = sb + OFF_Z + (uint32_t)((j + 2) & 3) * 20480u;
          uint32_t fb = BAR(B_FULL1 + (j & 7));
          mbar_expect_tx(fb, 20480);
          tma3d(dst, &tm.qkv, sl * 64, j * 32, 0, fb);
          tma2d(dst + 12288, &tm.w1, f0, j * 32, fb);
          tma2d(dst + 16384, &tm.w3, f0, j * 32, fb);
        }
        MARK(1);
        {
          auto unit = [&](int u, int slot) {
            uint32_t dst = sb + OFF_Z + 40960u + (uint32_t)slot * 8192u;
            uint32_t fb = BAR(B_FULL1 + ((16 + (u >> 1)) & 7));
            if (!(u & 1)) mbar_expect_tx(fb, 16384);
            if (u < 30) tma3d(dst, (u & 1) ? &tm.w3p : &tm.w1p, f0 + 64, (u >> 1) * 32, 0, fb);
            else {
              tma2d(dst, (u & 1) ? &tm.w3 : &tm.w1, f0 + 64, 480, fb);
              tma2d(dst + 4096, (u & 1) ? &tm.w3 : &tm.w1, f0 + 128, 480, fb);
            }
          };
          int slot = 5;
#pragma unroll 1
          for (int u = 0; u < 32; u++) {
            if (u == 2 || u == 4) mbar_wait(BAR(B_EMPTY1 + 3 + (u >> 1)), 1);
            else if (u >= 7 && (u & 1)) { int jj = 16 + ((u - 7) >> 1); mbar_wait(BAR(B_EMPTY1 + (jj & 7)), (jj >> 3) & 1); }
            unit(u, slot);
            slot = (slot == 6) ? 0 : slot + 1;
          }
        }
        MARK(2);
        const int colk = nq * 128 + kh * 64, cols = nq * 128 + (kh ^ 1) * 64;
#pragma unroll 1
        for (int n = 0; n < 16; n++) {
          const int t = c_btile[n];
          if (n == 0) mbar_wait(BAR(B_XFREE), 0);
          else if (n == 3) mbar_wait(BAR(B_EMPTY1 + (30 & 7)), 1);
          else if (n == 5) mbar_wait(BAR(B_EMPTY1 + (31 & 7)), 1);
          else if (t == 16) mbar_wait(BAR(B_H2RD), 0);
          const int pv = c_tile_prev[t];
          if (pv >= 0) mbar_wait(BAR(B_EMPTYT + pv), 0);
          const int kind = c_bkind[n] & 3, q = (nq + (c_bkind[n] >> 2)) & 3;
          const CUtensorMap* mp = kind == 3 ? &tm.wo : (kind == 2 ? &tm.w2t : &tm.w2);
          const int row = kind == 3 ? (kh * 4 + q) * 64 : kh * 688 + q * 176 + kind * 64;
          const uint32_t dst = sb + slot2_off(c_tile_slot[t]), fb = BAR(B_FULLT + t);
          mbar_expect_tx(fb, kind == 2 ? 12288u : 16384u);
          tma2d(dst, mp, colk, row, fb);
          tma2d(dst + 8192, mp, cols, row, fb);
        }
        MARK(5);
      }
    } else if (warp == 9 || warp == 10) {
      if (lane == 0) {
        const int w = warp - 9;
        const unsigned int epoch = *(volatile unsigned int*)&g_epoch;
        const int id = m * 8 + sl;
#pragma unroll 1
        for (int job = 0; job < 4; job++) {
          mbar_wait(BAR(B_H1 + 2 * job + w), 0);
          unsigned int* fl;
          if (job == 1) {
            bulk_red_add_f32(&g_kv[epoch & 1][sl * 2048], sb + OFF_STG + w * 12288, 8192);
            bulk_red_add_f32(&g_z[epoch & 1][sl * 128], sb + OFF_STG + w * 12288 + 8192, 512);
            fl = g_kvcnt + sl * 8;
          } else {
            unsigned char* dst = (job == 0 ? g_ha : (job == 2 ? g_hb : g_o)) + (size_t)id * 16384 + w * 8192;
            bulk_s2g(dst, sb + (job == 0 ? OFF_H1 : (job == 2 ? OFF_XN + 5 * 16384 : OFF_XN + 7 * 16384)) + w * 8192, 8192);
            if (job == 2) bulk_s2g(g_hc + (size_t)id * 12288 + w * 6144, sb + OFF_XN + 6 * 16384 + w * 8192, 6144);
            fl = (job == 0 ? g_flag_ha : (job == 2 ? g_flag_hb : g_flag_o)) + id * 8;
          }
          bulk_commit(); bulk_wait0();
          red_release_gpu(fl, 1);
          if (job == 1) mbar_arrive(BAR(B_KVDONE));
          if (job == 2) mbar_arrive(BAR(B_H2RD));
          MARK(1 + job);
        }
      }
    } else {
      {
        sts32(sb + OFF_ONES + lane * 4, 0x3F803F80u);
        const unsigned short* wp = reinterpret_cast<const unsigned short*>(wphi) + sl * 4 * 256;
#pragma unroll 4
        for (int i = lane; i < 1024; i += 32) {
          int h = i >> 8, d = (i >> 4) & 15, f = i & 15;
          sts16(sb + OFF_WPHI + h * 512 + (f >> 3) * 256 + (d >> 3) * 128 + (f & 7) * 16 + (d & 7) * 2, wp[i]);
        }
        fence_async_smem();
        mbar_arrive(BAR(B_WPHI));
      }
      const unsigned int epoch = *(volatile unsigned int*)&g_epoch;
      reinterpret_cast<float4*>(&g_kv[(epoch + 1) & 1][bid * 128])[lane] = make_float4(0.f, 0.f, 0.f, 0.f);
      if (lane < 8) g_z[(epoch + 1) & 1][bid * 8 + lane] = 0.f;
      if (lane == 0) {
        mbar_wait(BAR(B_XLAND), 0);
        pf3d(&tm.qkv, sl * 64, m * 32, 0);
        pf2d(&tm.w1, f0, m * 32);       pf2d(&tm.w3, f0, m * 32);
        __nanosleep(700);
        pf2d(&tm.w1, f0 + 64, m * 32);  pf2d(&tm.w3, f0 + 64, m * 32);
        pf2d(&tm.w1, f0 + 128, m * 32); pf2d(&tm.w3, f0 + 128, m * 32);
        __nanosleep(700);
#pragma unroll 1
        for (int i = bid; i < 240; i += 128) {
          if (i < 176) pf2d(&tm.w2, (i & 7) * 64, (i >> 3) * 64);
          else pf2d(&tm.wo, (i & 7) * 64, ((i - 176) >> 3) * 64);
        }
      }
      __syncwarp();
      const int grp = lane / 3, d = lane - grp * 3 + 1;
      const int id = m * 8 + kh * 4 + ((nq + d) & 3);
      int tile = grp == 0 ? 2 * d - 1 : (grp == 1 ? 5 + 4 * d : (grp == 2 ? 7 + 4 * d : 20 + 2 * d));
      const unsigned char* src = grp == 0 ? g_ha + (size_t)id * 16384 : (grp == 1 ? g_hb + (size_t)id * 16384 : (grp == 2 ? g_hc + (size_t)id * 12288 : g_o + (size_t)id * 16384));
      const unsigned int* flag = grp == 0 ? g_flag_ha + id * 8 : (grp == 3 ? g_flag_o + id * 8 : g_flag_hb + id * 8);
      unsigned int tgt = 2u * (epoch + 1u);
      if (lane == 12) { flag = g_kvcnt + sl * 8; tgt = 32u * (epoch + 1u); }
      if (lane > 11) tile = 9;
      const int pv = c_tile_prev[tile];
      const uint32_t wb = pv >= 0 ? BAR(B_EMPTYT + pv) : (tile == 5 ? BAR(B_KVB) : BAR(B_XFREE));
      int state = lane <= 12 ? 0 : 2;
      while (true) {
        if (state == 0 && (int)(ld_acquire_gpu(flag) - tgt) >= 0) state = 1;
        if (state == 1 && lane < 12 && mbar_test(wb, 0) && (tile != 9 || mbar_test(BAR(B_KVDONE), 0))) {
          uint32_t bytes = grp == 2 ? 12288u : 16384u;
          uint32_t fb = BAR(B_FULLT + tile);
          mbar_expect_tx(fb, bytes);
          bulk_g2s(sb + slot2_off(c_tile_slot[tile]), src, bytes, fb);
          state = 2;
        }
        unsigned kvrdy = __ballot_sync(0xffffffffu, lane == 12 && state == 1);
        if (kvrdy) {
          MARK(1);
          if (lane == 0) {
            mbar_expect_tx(BAR(B_KVRAW), 8704);
            bulk_g2s(sb + OFF_KVRAW, &g_kv[epoch & 1][sl * 2048], 8192, BAR(B_KVRAW));
            bulk_g2s(sb + OFF_KVRAW + 8192, &g_z[epoch & 1][sl * 128], 512, BAR(B_KVRAW));
          }
          mbar_wait(BAR(B_KVRAW), 0);
#pragma unroll 2
          for (int i = lane; i < 256; i += 32) {
            float4 v0 = lds128f(sb + OFF_KVRAW + i * 32), v1 = lds128f(sb + OFF_KVRAW + i * 32 + 16);
            int h = i >> 6, dd = (i >> 2) & 15, fo = i & 3;
            uint4 w; w.x = pack_bf16(v0.x, v0.y); w.y = pack_bf16(v0.z, v0.w); w.z = pack_bf16(v1.x, v1.y); w.w = pack_bf16(v1.z, v1.w);
            sts128(sb + OFF_KVB + h * 1536 + (fo >> 1) * 768 + (dd >> 3) * 256 + (fo & 1) * 128 + (dd & 7) * 16, w);
          }
          {
            const int h = lane >> 3, fo = (lane >> 1) & 3, half = lane & 1;
            float4 v0 = lds128f(sb + OFF_KVRAW + 8192 + h * 128 + fo * 32), v1 = lds128f(sb + OFF_KVRAW + 8192 + h * 128 + fo * 32 + 16);
            uint4 zz; zz.x = pack_bf16(v0.x, v0.y); zz.y = pack_bf16(v0.z, v0.w); zz.z = pack_bf16(v1.x, v1.y); zz.w = pack_bf16(v1.z, v1.w);
            uint32_t a = sb + OFF_KVB + h * 1536 + (fo >> 1) * 768 + 512 + (fo & 1) * 128 + half * 64;
            sts128(a, zz); sts128(a + 16, zz); sts128(a + 32, zz); sts128(a + 48, zz);
          }
          fence_async_smem();
          mbar_arrive(BAR(B_KVB));
          if (lane == 12) state = 2;
          MARK(3);
        }
        if (__all_sync(0xffffffffu, state == 2)) break;
        unsigned long long dl; asm volatile("ld.shared.u64 %0, [%1 + 1016];" : "=l"(dl) : "r"(bar0) : "memory");
        if (gtime() >= dl) break;
        __nanosleep(64);
      }
      MARK(2);
    }
    __syncwarp();
    teardown(false);
  } else {
    asm volatile("setmaxnreg.inc.sync.aligned.u32 232;");
    MARK(0);
    const int wg = warp >> 2, w4 = warp & 3;
    const int g = lane >> 2, t4 = lane & 3;
    const int tw = tid & 127;
    const uint32_t peer = (uint32_t)(kh ^ 1);
    {
      const int rsub = lane >> 3, sub = lane & 7;
      uint4 v[8], vn[8];
      const int row0 = kh * 64 + warp * 8 + rsub;
      const __nv_bfloat16* xb = x + (size_t)(m * 128 + row0) * D_ + sub * 8;
#pragma unroll
      for (int i = 0; i < 8; i++) v[i] = ldg128(xb + i * 64);
#pragma unroll
      for (int i = 0; i < 8; i++) vn[i] = ldg128(xb + 4 * D_ + i * 64);
      asm volatile("barrier.cluster.wait.aligned;" ::: "memory");
      const uint32_t rbar = mapa(BAR(B_XNR), peer);
      const uint32_t rsb = mapa(sb, peer);
#pragma unroll 1
      for (int gi = 0; gi < 2; gi++) {
        float s = 0.f;
#pragma unroll
        for (int i = 0; i < 8; i++) {
          s += (bf_lo(v[i].x) + bf_hi(v[i].x)) + (bf_lo(v[i].y) + bf_hi(v[i].y));
          s += (bf_lo(v[i].z) + bf_hi(v[i].z)) + (bf_lo(v[i].w) + bf_hi(v[i].w));
        }
        s += __shfl_xor_sync(0xffffffffu, s, 1);
        s += __shfl_xor_sync(0xffffffffu, s, 2);
        s += __shfl_xor_sync(0xffffffffu, s, 4);
        if (gi == 0 && lane == 0) mbar_arrive(BAR(B_XLAND));
        MARK(16 + gi);
        const float mean = s * (1.f / 512.f);
        float q0 = 0.f, q1 = 0.f;
#pragma unroll
        for (int i = 0; i < 8; i++) {
          const uint32_t* w = reinterpret_cast<const uint32_t*>(&v[i]);
#pragma unroll
          for (int e = 0; e < 4; e++) {
            float d0 = bf_lo(w[e]) - mean, d1 = bf_hi(w[e]) - mean;
            q0 = fmaf(d0, d0, q0); q1 = fmaf(d1, d1, q1);
          }
        }
        float q = q0 + q1;
        q += __shfl_xor_sync(0xffffffffu, q, 1);
        q += __shfl_xor_sync(0xffffffffu, q, 2);
        q += __shfl_xor_sync(0xffffffffu, q, 4);
        const float rstd = rsqrtf(q * (1.f / 512.f) + 1e-5f);
        const float nb = -mean * rstd;
        const int row = row0 + gi * 4;
        const uint32_t ro = OFF_XN + row * 128 + ((sub ^ (row & 7)) << 4);
#pragma unroll
        for (int i = 0; i < 8; i++) {
          const uint32_t* w = reinterpret_cast<const uint32_t*>(&v[i]);
          uint4 o;
          o.x = pack_bf16(fmaf(bf_lo(w[0]), rstd, nb), fmaf(bf_hi(w[0]), rstd, nb));
          o.y = pack_bf16(fmaf(bf_lo(w[1]), rstd, nb), fmaf(bf_hi(w[1]), rstd, nb));
          o.z = pack_bf16(fmaf(bf_lo(w[2]), rstd, nb), fmaf(bf_hi(w[2]), rstd, nb));
          o.w = pack_bf16(fmaf(bf_lo(w[3]), rstd, nb), fmaf(bf_hi(w[3]), rstd, nb));
          st_async4u(rsb + ro + i * 16384, o, rbar);
          sts128(sb + ro + i * 16384, o);
          v[i] = vn[i];
        }
      }
      fence_async_smem();
      mbar_arrive(BAR(B_XNL));
      if (wg == kh) mbar_wait(BAR(B_XNL), 0);
      else { mbar_wait_cluster(BAR(B_XNR), 0); fence_async_smem(); }
    }
    MARK(1);
    const uint64_t dA0 = mkdesc(sb + OFF_XN + wg * 8192, 16, 1024, 1);
    const uint32_t st_off = (uint32_t)((2 * w4 + ((lane >> 3) & 1)) * 256 + (lane >> 4) * 128 + (lane & 7) * 16);

    uint32_t qp[16], kp[16], vp[16], phq[4][8];
    const uint64_t dWP = mkdesc(sb + OFF_WPHI, 128, 256, 0);
    {
      float a_qkv[96], a_gu[64];
#pragma unroll 1
      for (int j = 0; j < 16; j++) {
        mbar_wait(BAR(B_FULL1 + (j & 7)), (j >> 3) & 1);
        uint32_t bs = sb + OFF_Z + (uint32_t)((j + 2) & 3) * 20480u;
        uint64_t dB = mkdesc(bs, 4096, 1024, 1);
        uint64_t dA = dA0 + (uint64_t)(((j >> 1) * 16384 + (j & 1) * 64) >> 4);
        wg_fence();
        wgmma_n192(a_qkv, dA, dB, j > 0);
        wgmma_n128(a_gu, dA, dB + (12288 >> 4), j > 0);
        wgmma_n192(a_qkv, dA + 2, dB + (2048 >> 4), 1);
        wgmma_n128(a_gu, dA + 2, dB + ((12288 + 2048) >> 4), 1);
        wg_commit();
        if (j > 0) { wg_wait<1>(); if (lane == 0) mbar_arrive(BAR(B_EMPTY1 + ((j - 1) & 7))); }
      }
      wg_wait<0>();
      MARK(2);
      if (lane == 0) mbar_arrive(BAR(B_EMPTY1 + 7));
#pragma unroll
      for (int i = 0; i < 16; i++) {
        qp[i] = pack_bf16(a_qkv[2 * i], a_qkv[2 * i + 1]);
        kp[i] = pack_bf16(a_qkv[32 + 2 * i], a_qkv[32 + 2 * i + 1]);
        vp[i] = pack_bf16(a_qkv[64 + 2 * i], a_qkv[64 + 2 * i + 1]);
      }
      uint32_t rr[16];
#pragma unroll
      for (int e = 0; e < 16; e++)
        rr[e] = pack_bf16(silu_mul(a_gu[2 * e], a_gu[32 + 2 * e]), silu_mul(a_gu[2 * e + 1], a_gu[32 + 2 * e + 1]));
      mbar_wait(BAR(B_EMPTY1 + 6), 1);
      mbar_wait(BAR(B_EMPTY1 + 7), 1);
      const uint32_t hb = sb + OFF_H1 + wg * 8192 + st_off;
#pragma unroll
      for (int kb = 0; kb < 4; kb++) stsm4(hb + kb * 2048, rr[4 * kb], rr[4 * kb + 1], rr[4 * kb + 2], rr[4 * kb + 3]);
      fence_async_smem();
      mbar_arrive(BAR(B_H1 + wg));
    }
    MARK(3);
    {
      float ag[64], au[56];
      pass2(wg, ag, au, qp, kp, vp, phq, sb, bar0, dA0, dWP, lane, w4, bid);
      wg_wait<0>();
      MARK(5);
      if (lane == 0) mbar_arrive(BAR(B_EMPTY1 + 7));
#pragma unroll
      for (int e = 56; e < 64; e++) KEEPF(ag[e]);
      named_bar(1 + wg, 128);
      const uint32_t hb = sb + OFF_XN + 5 * 16384 + wg * 8192 + st_off;
#pragma unroll
      for (int kb = 0; kb < 7; kb++) {
        uint32_t rr[4];
#pragma unroll
        for (int e = 0; e < 4; e++) {
          int idx = kb * 8 + e * 2;
          rr[e] = pack_bf16(silu_mul(ag[idx], au[idx]), silu_mul(ag[idx + 1], au[idx + 1]));
          if (kb == 6 && nq == 3) rr[e] = 0u;
        }
        stsm4(hb + (kb < 4 ? kb * 2048 : 16384 + (kb - 4) * 2048), rr[0], rr[1], rr[2], rr[3]);
      }
      fence_async_smem();
      mbar_arrive(BAR(B_H2 + wg));
      named_bar(1 + wg, 128);
    }
    MARK(6);
    {
      float a_o[64], a_s[64];
      const uint32_t own_ha = sb + OFF_H1 + wg * 8192;
      const uint32_t own_hb = sb + OFF_XN + 5 * 16384 + wg * 8192;
      const uint32_t own_hc = sb + OFF_XN + 6 * 16384 + wg * 8192;
      const uint32_t own_o  = sb + OFF_XN + 7 * 16384 + wg * 8192;
      {
        p2_step<-1, 0, 4, 1, -1, -1, 0>(a_o, sb, bar0, own_ha, lane);
        mbar_wait(BAR(B_KVB), 0);
        MARK(7);
        float nd[4][12];
        const uint64_t dKV = mkdesc(sb + OFF_KVB, 128, 256, 0);
        p2_issue<1, 2, 4, 0>(a_o, sb, bar0, wg * 8192);
#pragma unroll
        for (int h = 0; h < 4; h++) {
          wgmma_rs_n24(nd[h], phq[h][0], phq[h][1], phq[h][2], phq[h][3], dKV + h * 96, 0);
          wgmma_rs_n24(nd[h], phq[h][4], phq[h][5], phq[h][6], phq[h][7], dKV + h * 96 + 48, 1);
        }
        p2_commit<-1, 0, 1>(bar0, lane);
        p2_step<3, 4, 4, 0, 1, 2, 1>(a_o, sb, bar0, wg * 8192, lane);
#pragma unroll
        for (int h = 0; h < 4; h++) {
          float r0 = rcp(0.5f * (nd[h][8] + nd[h][9]) + 1e-6f), r1 = rcp(0.5f * (nd[h][10] + nd[h][11]) + 1e-6f);
          stsm4(own_o + st_off + h * 2048, pack_bf16(nd[h][0] * r0, nd[h][1] * r0), pack_bf16(nd[h][2] * r1, nd[h][3] * r1),
                pack_bf16(nd[h][4] * r0, nd[h][5] * r0), pack_bf16(nd[h][6] * r1, nd[h][7] * r1));
        }
        fence_async_smem();
        mbar_arrive(BAR(B_O + wg));
        p2_step<5, 6, 4, 0, 3, 4, 1>(a_o, sb, bar0, wg * 8192, lane);
        named_bar(1 + wg, 128);
      }
      MARK(9);
      p2_step<-1, 7, 4, 0, 5, -1, 1>(a_o, sb, bar0, own_hb, lane);
      p2_step<-1, 8, 3, 0, -1, 7, 1>(a_o, sb, bar0, own_hc, lane);
      p2_step<9, 10, 4, 0, -1, 8, 1>(a_o, sb, bar0, wg * 8192, lane);
      if (lane == 0) mbar_arrive_remote(mapa(BAR(B_XO_OK), peer));
      p2_step<11, 12, 3, 0, 9, 10, 1>(a_o, sb, bar0, wg * 6144, lane);
      p2_step<13, 14, 4, 0, 11, 12, 1>(a_o, sb, bar0, wg * 8192, lane);
      p2_step<15, 16, 3, 0, 13, 14, 1>(a_o, sb, bar0, wg * 6144, lane);
      p2_step<17, 18, 4, 0, -1, 16, 1>(a_o, sb, bar0, wg * 8192, lane);
      p2_step<19, 20, 3, 0, -1, 18, 1>(a_o, sb, bar0, wg * 6144, lane);
      if (lane == 0) mbar_arrive_remote(mapa(BAR(B_XS_OK), peer));
      uint32_t xr[16];
      {
        const uint32_t* xp = reinterpret_cast<const uint32_t*>(x + (size_t)(m * 128 + wg * 64 + w4 * 16 + g) * D_ + nq * 128 + kh * 64 + t4 * 2);
#pragma unroll
        for (int j = 0; j < 8; j++) { xr[2 * j] = __ldg(xp + j * 4); xr[2 * j + 1] = __ldg(xp + 8 * (D_ / 2) + j * 4); }
      }
      MARK(10);
      p2_step<-1, 21, 4, 1, 19, -1, 1>(a_s, sb, bar0, own_o, lane);
      {
        mbar_wait_cluster(BAR(B_XO_OK), 0);
        uint32_t ra = mapa(sb + OFF_XO_RECV + wg * 16384 + tw * 16, peer), rb = mapa(BAR(B_XO_FULL + wg), peer);
#pragma unroll
        for (int i = 0; i < 8; i++) st_async4(ra + i * 2048, a_o[32 + 4 * i], a_o[33 + 4 * i], a_o[34 + 4 * i], a_o[35 + 4 * i], rb);
      }
      p2_step<22, 23, 4, 0, -1, -1, 0>(a_s, sb, bar0, wg * 8192, lane);
      p2_step<24, 25, 4, 0, -1, -1, 0>(a_s, sb, bar0, wg * 8192, lane);
      mbar_wait_cluster(BAR(B_XO_FULL + wg), 0);
      float gt[32];
#pragma unroll
      for (int i = 0; i < 8; i++) {
        float4 v = lds128f(sb + OFF_XO_RECV + wg * 16384 + tw * 16 + i * 2048);
        float o0 = a_o[4 * i] + v.x, o1 = a_o[4 * i + 1] + v.y, o2 = a_o[4 * i + 2] + v.z, o3 = a_o[4 * i + 3] + v.w;
        gt[4 * i] = silu_mul(o0, 1.f); gt[4 * i + 1] = silu_mul(o1, 1.f); gt[4 * i + 2] = silu_mul(o2, 1.f); gt[4 * i + 3] = silu_mul(o3, 1.f);
      }
      p2_step<26, 27, 4, 0, -1, -1, 0>(a_s, sb, bar0, wg * 8192, lane);
      MARK(11);
      wg_wait<0>();
      MARK(12);
      {
        mbar_wait_cluster(BAR(B_XS_OK), 0);
        uint32_t ra = mapa(sb + OFF_XS_RECV + wg * 16384 + tw * 16, peer), rb = mapa(BAR(B_XS_FULL + wg), peer);
#pragma unroll
        for (int i = 0; i < 8; i++) st_async4(ra + i * 2048, a_s[32 + 4 * i], a_s[33 + 4 * i], a_s[34 + 4 * i], a_s[35 + 4 * i], rb);
      }
      MARK(13);
      mbar_wait_cluster(BAR(B_XS_FULL + wg), 0);
      MARK(14);
      uint32_t* op = reinterpret_cast<uint32_t*>(out + (size_t)(m * 128 + wg * 64 + w4 * 16 + g) * D_ + nq * 128 + kh * 64 + t4 * 2);
#pragma unroll
      for (int i = 0; i < 8; i++) {
        float4 v = lds128f(sb + OFF_XS_RECV + wg * 16384 + tw * 16 + i * 2048);
        float y0 = fmaf(a_s[4 * i] + v.x, gt[4 * i], bf_lo(xr[2 * i]));
        float y1 = fmaf(a_s[4 * i + 1] + v.y, gt[4 * i + 1], bf_hi(xr[2 * i]));
        float y2 = fmaf(a_s[4 * i + 2] + v.z, gt[4 * i + 2], bf_lo(xr[2 * i + 1]));
        float y3 = fmaf(a_s[4 * i + 3] + v.w, gt[4 * i + 3], bf_hi(xr[2 * i + 1]));
        op[i * 4] = pack_bf16(y0, y1);
        op[8 * (D_ / 2) + i * 4] = pack_bf16(y2, y3);
      }
    }
    MARK(15);
    teardown(tid == 0);
  }
}

typedef CUresult (*EncFn)(CUtensorMap*, CUtensorMapDataType, cuuint32_t, void*, const cuuint64_t*, const cuuint64_t*, const cuuint32_t*,
                          const cuuint32_t*, CUtensorMapInterleave, CUtensorMapSwizzle, CUtensorMapL2promotion, CUtensorMapFloatOOBfill);

void enc(EncFn fn, CUtensorMap* tm, const void* base, int rank, const cuuint64_t* gd, const cuuint64_t* gs, const cuuint32_t* bd) {
  cuuint32_t es[3] = {1, 1, 1};
  CUresult rc = fn(tm, CU_TENSOR_MAP_DATA_TYPE_BFLOAT16, (cuuint32_t)rank, const_cast<void*>(base), gd, gs, bd, es, CU_TENSOR_MAP_INTERLEAVE_NONE,
                   CU_TENSOR_MAP_SWIZZLE_128B, CU_TENSOR_MAP_L2_PROMOTION_L2_128B, CU_TENSOR_MAP_FLOAT_OOB_FILL_NONE);
  (void)rc;
}

}

extern "C" void kernel_launch(void* const* d_in, const int* in_sizes, int n_in, void* d_out, int out_size) {
  const __nv_bfloat16* x    = (const __nv_bfloat16*)d_in[0];
  const __nv_bfloat16* wqkv = (const __nv_bfloat16*)d_in[1];
  const __nv_bfloat16* wphi = (const __nv_bfloat16*)d_in[2];
  const __nv_bfloat16* wo   = (const __nv_bfloat16*)d_in[3];
  const __nv_bfloat16* w1   = (const __nv_bfloat16*)d_in[5];
  const __nv_bfloat16* w3   = (const __nv_bfloat16*)d_in[6];
  const __nv_bfloat16* w2   = (const __nv_bfloat16*)d_in[7];

  static EncFn fn = nullptr;
  if (!fn) {
    void* p = nullptr; cudaDriverEntryPointQueryResult qr;
    cudaGetDriverEntryPoint("cuTensorMapEncodeTiled", &p, cudaEnableDefault, &qr);
    fn = (EncFn)p;
    cudaFuncSetAttribute(fused_kernel, cudaFuncAttributeMaxDynamicSharedMemorySize, SMEM_BYTES);
  }
  TMaps tm;
  { cuuint64_t gd[3] = {512, 512, 3}; cuuint64_t gs[2] = {3072, 1024}; cuuint32_t bd[3] = {64, 32, 3};
    enc(fn, &tm.qkv, wqkv, 3, gd, gs, bd); }
  { cuuint64_t gd[2] = {F_, 512}; cuuint64_t gs[1] = {F_ * 2}; cuuint32_t bd[2] = {64, 32};
    enc(fn, &tm.w1, w1, 2, gd, gs, bd);  enc(fn, &tm.w3, w3, 2, gd, gs, bd);
  }
  { cuuint64_t gd[3] = {F_, 512, 2}; cuuint64_t gs[2] = {F_ * 2, 128}; cuuint32_t bd[3] = {64, 32, 2};
    enc(fn, &tm.w1p, w1, 3, gd, gs, bd); enc(fn, &tm.w3p, w3, 3, gd, gs, bd); }
  { cuuint64_t gd[2] = {512, F_}; cuuint64_t gs[1] = {1024}; cuuint32_t bd[2] = {64, 64}; cuuint32_t bd2[2] = {64, 48};
    enc(fn, &tm.w2, w2, 2, gd, gs, bd); enc(fn, &tm.w2t, w2, 2, gd, gs, bd2); }
  { cuuint64_t gd[2] = {512, 512}; cuuint64_t gs[1] = {1024}; cuuint32_t bd[2] = {64, 64};
    enc(fn, &tm.wo, wo, 2, gd, gs, bd); }

  cudaLaunchConfig_t cfg = {};
  cfg.gridDim = dim3(128); cfg.blockDim = dim3(384); cfg.dynamicSmemBytes = SMEM_BYTES; cfg.stream = cudaStreamPerThread;
  cudaLaunchKernelEx(&cfg, fused_kernel, tm, x, wphi, (__nv_bfloat16*)d_out);
}
```

```cpp
#include <cuda_runtime.h>
#include <cuda_bf16.h>
#include <cuda.h>
#include <stdint.h>

__device__ __forceinline__ void wgmma_n64(float (&d)[32], uint64_t da, uint64_t db, int scale_d) {
  asm volatile("{\n.reg .pred p;\nsetp.ne.b32 p, %34, 0;\n"
  "wgmma.mma_async.sync.aligned.m64n64k16.f32.bf16.bf16 {%0, %1, %2, %3, %4, %5, %6, %7, %8, %9, %10, %11, %12, %13, %14, %15, %16, %17, %18, %19, %20, %21, %22, %23, %24, %25, %26, %27, %28, %29, %30, %31}, %32, %33, p, 1, 1, 0, 1;\n}\n"
  : "+f"(d[0]), "+f"(d[1]), "+f"(d[2]), "+f"(d[3]), "+f"(d[4]), "+f"(d[5]), "+f"(d[6]), "+f"(d[7]), "+f"(d[8]), "+f"(d[9]), "+f"(d[10]), "+f"(d[11]), "+f"(d[12]), "+f"(d[13]), "+f"(d[14]), "+f"(d[15]), "+f"(d[16]), "+f"(d[17]), "+f"(d[18]), "+f"(d[19]), "+f"(d[20]), "+f"(d[21]), "+f"(d[22]), "+f"(d[23]), "+f"(d[24]), "+f"(d[25]), "+f"(d[26]), "+f"(d[27]), "+f"(d[28]), "+f"(d[29]), "+f"(d[30]), "+f"(d[31]) : "l"(da), "l"(db), "r"(scale_d));
}
__device__ __forceinline__ void wgmma_n48(float (&d)[24], uint64_t da, uint64_t db, int scale_d) {
  asm volatile("{\n.reg .pred p;\nsetp.ne.b32 p, %26, 0;\n"
  "wgmma.mma_async.sync.aligned.m64n48k16.f32.bf16.bf16 {%0, %1, %2, %3, %4, %5, %6, %7, %8, %9, %10, %11, %12, %13, %14, %15, %16, %17, %18, %19, %20, %21, %22, %23}, %24, %25, p, 1, 1, 0, 1;\n}\n"
  : "+f"(d[0]), "+f"(d[1]), "+f"(d[2]), "+f"(d[3]), "+f"(d[4]), "+f"(d[5]), "+f"(d[6]), "+f"(d[7]), "+f"(d[8]), "+f"(d[9]), "+f"(d[10]), "+f"(d[11]), "+f"(d[12]), "+f"(d[13]), "+f"(d[14]), "+f"(d[15]), "+f"(d[16]), "+f"(d[17]), "+f"(d[18]), "+f"(d[19]), "+f"(d[20]), "+f"(d[21]), "+f"(d[22]), "+f"(d[23]) : "l"(da), "l"(db), "r"(scale_d));
}
__device__ __forceinline__ void wgmma_n128(float (&d)[64], uint64_t da, uint64_t db, int scale_d) {
  asm volatile("{\n.reg .pred p;\nsetp.ne.b32 p, %66, 0;\n"
  "wgmma.mma_async.sync.aligned.m64n128k16.f32.bf16.bf16 {%0, %1, %2, %3, %4, %5, %6, %7, %8, %9, %10, %11, %12, %13, %14, %15, %16, %17, %18, %19, %20, %21, %22, %23, %24, %25, %26, %27, %28, %29, %30, %31, %32, %33, %34, %35, %36, %37, %38, %39, %40, %41, %42, %43, %44, %45, %46, %47, %48, %49, %50, %51, %52, %53, %54, %55, %56, %57, %58, %59, %60, %61, %62, %63}, %64, %65, p, 1, 1, 0, 1;\n}\n"
  : "+f"(d[0]), "+f"(d[1]), "+f"(d[2]), "+f"(d[3]), "+f"(d[4]), "+f"(d[5]), "+f"(d[6]), "+f"(d[7]), "+f"(d[8]), "+f"(d[9]), "+f"(d[10]), "+f"(d[11]), "+f"(d[12]), "+f"(d[13]), "+f"(d[14]), "+f"(d[15]), "+f"(d[16]), "+f"(d[17]), "+f"(d[18]), "+f"(d[19]), "+f"(d[20]), "+f"(d[21]), "+f"(d[22]), "+f"(d[23]), "+f"(d[24]), "+f"(d[25]), "+f"(d[26]), "+f"(d[27]), "+f"(d[28]), "+f"(d[29]), "+f"(d[30]), "+f"(d[31]), "+f"(d[32]), "+f"(d[33]), "+f"(d[34]), "+f"(d[35]), "+f"(d[36]), "+f"(d[37]), "+f"(d[38]), "+f"(d[39]), "+f"(d[40]), "+f"(d[41]), "+f"(d[42]), "+f"(d[43]), "+f"(d[44]), "+f"(d[45]), "+f"(d[46]), "+f"(d[47]), "+f"(d[48]), "+f"(d[49]), "+f"(d[50]), "+f"(d[51]), "+f"(d[52]), "+f"(d[53]), "+f"(d[54]), "+f"(d[55]), "+f"(d[56]), "+f"(d[57]), "+f"(d[58]), "+f"(d[59]), "+f"(d[60]), "+f"(d[61]), "+f"(d[62]), "+f"(d[63]) : "l"(da), "l"(db), "r"(scale_d));
}
__device__ __forceinline__ void wgmma_n32_tt(float (&d)[16], uint64_t da, uint64_t db, int scale_d) {
  asm volatile("{\n.reg .pred p;\nsetp.ne.b32 p, %18, 0;\n"
  "wgmma.mma_async.sync.aligned.m64n32k16.f32.bf16.bf16 {%0, %1, %2, %3, %4, %5, %6, %7, %8, %9, %10, %11, %12, %13, %14, %15}, %16, %17, p, 1, 1, 1, 1;\n}\n"
  : "+f"(d[0]), "+f"(d[1]), "+f"(d[2]), "+f"(d[3]), "+f"(d[4]), "+f"(d[5]), "+f"(d[6]), "+f"(d[7]), "+f"(d[8]), "+f"(d[9]), "+f"(d[10]), "+f"(d[11]), "+f"(d[12]), "+f"(d[13]), "+f"(d[14]), "+f"(d[15]) : "l"(da), "l"(db), "r"(scale_d));
}
__device__ __forceinline__ void wgmma_n8_tt(float (&d)[4], uint64_t da, uint64_t db, int scale_d) {
  asm volatile("{\n.reg .pred p;\nsetp.ne.b32 p, %6, 0;\n"
  "wgmma.mma_async.sync.aligned.m64n8k16.f32.bf16.bf16 {%0, %1, %2, %3}, %4, %5, p, 1, 1, 1, 1;\n}\n"
  : "+f"(d[0]), "+f"(d[1]), "+f"(d[2]), "+f"(d[3]) : "l"(da), "l"(db), "r"(scale_d));
}
__device__ __forceinline__ void wgmma_rs_n16(float (&d)[8], uint32_t a0, uint32_t a1, uint32_t a2, uint32_t a3, uint64_t db, int scale_d) {
  asm volatile("{\n.reg .pred p;\nsetp.ne.b32 p, %13, 0;\n"
  "wgmma.mma_async.sync.aligned.m64n16k16.f32.bf16.bf16 {%0, %1, %2, %3, %4, %5, %6, %7}, {%8, %9, %10, %11}, %12, p, 1, 1, 0;\n}\n"
  : "+f"(d[0]), "+f"(d[1]), "+f"(d[2]), "+f"(d[3]), "+f"(d[4]), "+f"(d[5]), "+f"(d[6]), "+f"(d[7]) : "r"(a0), "r"(a1), "r"(a2), "r"(a3), "l"(db), "r"(scale_d));
}
__device__ __forceinline__ void wgmma_rs_n24(float (&d)[12], uint32_t a0, uint32_t a1, uint32_t a2, uint32_t a3, uint64_t db, int scale_d) {
  asm volatile("{\n.reg .pred p;\nsetp.ne.b32 p, %17, 0;\n"
  "wgmma.mma_async.sync.aligned.m64n24k16.f32.bf16.bf16 {%0, %1, %2, %3, %4, %5, %6, %7, %8, %9, %10, %11}, {%12, %13, %14, %15}, %16, p, 1, 1, 0;\n}\n"
  : "+f"(d[0]), "+f"(d[1]), "+f"(d[2]), "+f"(d[3]), "+f"(d[4]), "+f"(d[5]), "+f"(d[6]), "+f"(d[7]), "+f"(d[8]), "+f"(d[9]), "+f"(d[10]), "+f"(d[11]) : "r"(a0), "r"(a1), "r"(a2), "r"(a3), "l"(db), "r"(scale_d));
}

namespace {

constexpr int S_ = 2048, D_ = 512, F_ = 1376;

constexpr uint32_t OFF_XN   = 0;
constexpr uint32_t OFF_R    = 131072;
constexpr uint32_t OFF_HA   = OFF_R + 65536;
constexpr uint32_t OFF_HC   = OFF_HA + 16384;
constexpr uint32_t OFF_HB   = OFF_XN + 6 * 16384;
constexpr uint32_t OFF_OO   = OFF_XN + 7 * 16384;
constexpr uint32_t OFF_KVB  = OFF_XN;
constexpr uint32_t OFF_KVRAW = OFF_XN + 6144;
constexpr uint32_t OFF_MISC = OFF_R + 98304;
constexpr uint32_t OFF_BAR  = OFF_MISC;
constexpr uint32_t OFF_ONES = OFF_MISC + 864;
constexpr uint32_t OFF_WPHI = OFF_MISC + 1024;
constexpr uint32_t SMEM_BYTES = OFF_MISC + 3072;

constexpr int B_FULL1 = 0, B_EMPTY1 = 16;
constexpr int B_FULLT = 32;
constexpr int B_EMPTYT = 60;
constexpr int B_KV = 79, B_HC = 80, B_HA = 81, B_HB = 82, B_O = 83;
constexpr int B_KVDONE = 84, B_HBRD = 85, B_KVB = 86, B_XO_OK = 87, B_XS_OK = 88, B_XO_FULL = 89, B_XS_FULL = 91;
constexpr int B_WPHI = 93, B_XNL = 94, B_XNR = 95, B_XLAND = 96, B_KVRAW = 97, B_STGFREE = 98, B_XF = 99;
constexpr int B_HCRD = 105, B_HARD = 106;
constexpr int NBAR = 107;

__host__ __device__ constexpr uint32_t slot2_off(int s) {
  return s < 7 ? (uint32_t)s * 16384u : OFF_R + (uint32_t)(s - 7) * 16384u;
}
constexpr uint32_t OFF_XS_RECV = OFF_R;
constexpr uint32_t OFF_XO_RECV = OFF_R + 32768;
#define TILE_SLOTS {1, 2, 3, 4, 5, 7, 8, 9, 10, 12, 1, 2, 3, 4, 5, 7, 8, 11, 0, 12, 1, 2, 3, 4, 5, 6, 11, 0}
#define TILE_PREVS {-1, -1, -1, -1, -1, -1, -1, -1, -1, 0, 0, 1, 2, 3, 4, 5, 6, 7, -1, 9, 10, 11, 12, 13, 14, 14, 17, 18}
__host__ __device__ constexpr int tile_slot(int t) { constexpr int tb[28] = TILE_SLOTS; return tb[t]; }
__device__ __constant__ signed char c_tile_slot[28] = TILE_SLOTS;
__device__ __constant__ signed char c_tile_prev[28] = TILE_PREVS;
__host__ __device__ constexpr int stage_unit0(int s) { return s < 8 ? 2 * s : (s < 16 ? 16 + 3 * (s - 8) : 40 + 2 * (s - 16)); }
__device__ __constant__ signed char c_stage_dep[32] = {-1, -1, -1, -1, 0, 1, 2, 3,   5, 6, 8, 9, 10, 11, 12, 13,   13, 14, 15, 15, 16, 17, 18, 19,   20, 21, 22, 23, 24, 25, 26, 27};

__device__ __align__(1024) unsigned char g_ha[16 * 8 * 16384];
__device__ __align__(1024) unsigned char g_hb[16 * 8 * 16384];
__device__ __align__(1024) unsigned char g_hc[16 * 8 * 12288];
__device__ __align__(1024) unsigned char g_o [16 * 8 * 16384];
__device__ __align__(1024) float g_kv[2][32 * 512];
__device__ __align__(1024) float g_z [2][32 * 32];
__device__ unsigned int g_flag_ha[128 * 8];
__device__ unsigned int g_flag_hb[128 * 8];
__device__ unsigned int g_flag_hc[128 * 8];
__device__ unsigned int g_flag_o [128 * 8];
__device__ unsigned int g_kvcnt[8 * 8];
__device__ unsigned int g_epoch;
__device__ unsigned int g_done;

#define MARK(i)
#define TRC(i)
#define TRP(i)

struct TMaps {
  CUtensorMap kv, q, w1, w3, w2, w2t, wo;
};

__device__ __forceinline__ uint32_t smem_u32(const void* p) { return (uint32_t)__cvta_generic_to_shared(p); }
__device__ __forceinline__ void mbar_init(uint32_t bar, int cnt) { asm volatile("mbarrier.init.shared::cta.b64 [%0], %1;" ::"r"(bar), "r"(cnt)); }
__device__ __forceinline__ void mbar_expect_tx(uint32_t bar, uint32_t bytes) { asm volatile("mbarrier.arrive.expect_tx.shared::cta.b64 _, [%0], %1;" ::"r"(bar), "r"(bytes) : "memory"); }
__device__ __forceinline__ void mbar_arrive(uint32_t bar) { asm volatile("mbarrier.arrive.shared::cta.b64 _, [%0];" ::"r"(bar) : "memory"); }
__device__ __forceinline__ void mbar_wait(uint32_t bar, uint32_t parity) {
  asm volatile("{\n.reg .pred p;\n.reg .u64 t, d;\n.reg .u32 a;\n"
               "WAIT_LOOP:\nmbarrier.try_wait.parity.shared::cta.b64 p, [%0], %1;\n@p bra WAIT_DONE;\n"
               "and.b32 a, %0, 0xFFFFFC00;\nld.shared.u64 d, [a + 1016];\nmov.u64 t, %%globaltimer;\nsetp.lt.u64 p, t, d;\n@p bra WAIT_LOOP;\nWAIT_DONE:\n}\n" ::"r"(bar), "r"(parity) : "memory");
}
__device__ __forceinline__ void mbar_wait_cluster(uint32_t bar, uint32_t parity) {
  asm volatile("{\n.reg .pred p;\n.reg .u64 t, d;\n.reg .u32 a;\n"
               "WAIT_LOOP:\nmbarrier.try_wait.parity.acquire.cluster.shared::cta.b64 p, [%0], %1;\n@p bra WAIT_DONE;\n"
               "and.b32 a, %0, 0xFFFFFC00;\nld.shared.u64 d, [a + 1016];\nmov.u64 t, %%globaltimer;\nsetp.lt.u64 p, t, d;\n@p bra WAIT_LOOP;\nWAIT_DONE:\n}\n" ::"r"(bar), "r"(parity) : "memory");
}
__device__ __forceinline__ unsigned long long gtime() { unsigned long long t; asm volatile("mov.u64 %0, %%globaltimer;" : "=l"(t)); return t; }
__device__ __forceinline__ uint32_t mapa(uint32_t addr, uint32_t cta) { uint32_t r; asm volatile("mapa.shared::cluster.u32 %0, %1, %2;" : "=r"(r) : "r"(addr), "r"(cta)); return r; }
__device__ __forceinline__ void mbar_arrive_remote(uint32_t raddr) { asm volatile("mbarrier.arrive.shared::cluster.b64 _, [%0];" ::"r"(raddr) : "memory"); }
__device__ __forceinline__ void tma2d(uint32_t dst, const CUtensorMap* tm, int c0, int c1, uint32_t bar) {
  asm volatile("cp.async.bulk.tensor.2d.shared::cluster.global.mbarrier::complete_tx::bytes [%0], [%1, {%3, %4}], [%2];" ::"r"(dst), "l"(tm), "r"(bar), "r"(c0), "r"(c1) : "memory");
}
__device__ __forceinline__ void tma3d(uint32_t dst, const CUtensorMap* tm, int c0, int c1, int c2, uint32_t bar) {
  asm volatile("cp.async.bulk.tensor.3d.shared::cluster.global.mbarrier::complete_tx::bytes [%0], [%1, {%3, %4, %5}], [%2];" ::"r"(dst), "l"(tm), "r"(bar), "r"(c0), "r"(c1), "r"(c2) : "memory");
}
__device__ __forceinline__ void pf2d(const CUtensorMap* tm, int c0, int c1) {
  asm volatile("cp.async.bulk.prefetch.tensor.2d.L2.global [%0, {%1, %2}];" ::"l"(tm), "r"(c0), "r"(c1) : "memory");
}
__device__ __forceinline__ void pf3d(const CUtensorMap* tm, int c0, int c1, int c2) {
  asm volatile("cp.async.bulk.prefetch.tensor.3d.L2.global [%0, {%1, %2, %3}];" ::"l"(tm), "r"(c0), "r"(c1), "r"(c2) : "memory");
}
__device__ __forceinline__ void bulk_g2s(uint32_t dst, const void* src, uint32_t bytes, uint32_t bar) {
  asm volatile("cp.async.bulk.shared::cluster.global.mbarrier::complete_tx::bytes [%0], [%1], %2, [%3];" ::"r"(dst), "l"(src), "r"(bytes), "r"(bar) : "memory");
}
__device__ __forceinline__ void bulk_s2g(void* dst, uint32_t src, uint32_t bytes) {
  asm volatile("cp.async.bulk.global.shared::cta.bulk_group [%0], [%1], %2;" ::"l"(dst), "r"(src), "r"(bytes) : "memory");
}
__device__ __forceinline__ void bulk_red_add_f32(void* dst, uint32_t src, uint32_t bytes) {
  asm volatile("cp.reduce.async.bulk.global.shared::cta.bulk_group.add.f32 [%0], [%1], %2;" ::"l"(dst), "r"(src), "r"(bytes) : "memory");
}
__device__ __forceinline__ void bulk_commit() { asm volatile("cp.async.bulk.commit_group;" ::: "memory"); }
__device__ __forceinline__ void bulk_wait0() { asm volatile("cp.async.bulk.wait_group 0;" ::: "memory"); }
__device__ __forceinline__ void fence_async_smem() { asm volatile("fence.proxy.async.shared::cta;" ::: "memory"); }
__device__ __forceinline__ void fence_async_all() { asm volatile("fence.proxy.async;" ::: "memory"); }
__device__ __forceinline__ void red_release_gpu(unsigned int* p, unsigned int v) { asm volatile("red.release.gpu.global.add.u32 [%0], %1;" ::"l"(p), "r"(v) : "memory"); }
__device__ __forceinline__ unsigned int ld_acquire_gpu(const unsigned int* p) { unsigned int v; asm volatile("ld.acquire.gpu.global.u32 %0, [%1];" : "=r"(v) : "l"(p) : "memory"); return v; }
__device__ __forceinline__ void wait_flag(const unsigned int* p, unsigned int target, uint32_t bar0) {
  while ((int)(ld_acquire_gpu(p) - target) < 0) {
    unsigned long long d; asm volatile("ld.shared.u64 %0, [%1 + 1016];" : "=l"(d) : "r"(bar0) : "memory");
    if (gtime() >= d) break;
  }
}
__device__ __forceinline__ void wg_fence() { asm volatile("wgmma.fence.sync.aligned;" ::: "memory"); }
__device__ __forceinline__ void wg_commit() { asm volatile("wgmma.commit_group.sync.aligned;" ::: "memory"); }
template <int N> __device__ __forceinline__ void wg_wait() { asm volatile("wgmma.wait_group.sync.aligned %0;" ::"n"(N) : "memory"); }
__device__ __forceinline__ void named_bar(int id, int n) { asm volatile("bar.sync %0, %1;" ::"r"(id), "r"(n) : "memory"); }
__device__ __forceinline__ uint64_t mkdesc(uint32_t addr, uint32_t lbo, uint32_t sbo, uint32_t mode) {
  return (uint64_t)((addr & 0x3FFFF) >> 4) | ((uint64_t)(lbo >> 4) << 16) | ((uint64_t)(sbo >> 4) << 32) | ((uint64_t)mode << 62);
}
__device__ __forceinline__ uint32_t pack_bf16(float lo, float hi) { uint32_t r; asm("cvt.rn.bf16x2.f32 %0, %1, %2;" : "=r"(r) : "f"(hi), "f"(lo)); return r; }
__device__ __forceinline__ float bf_lo(uint32_t v) { return __uint_as_float(v << 16); }
__device__ __forceinline__ float bf_hi(uint32_t v) { return __uint_as_float(v & 0xFFFF0000u); }
__device__ __forceinline__ float ex2(float x) { float r; asm("ex2.approx.ftz.f32 %0, %1;" : "=f"(r) : "f"(x)); return r; }
__device__ __forceinline__ float rcp(float x) { float r; asm("rcp.approx.ftz.f32 %0, %1;" : "=f"(r) : "f"(x)); return r; }
__device__ __forceinline__ float tanh_a(float x) { float r; asm("tanh.approx.f32 %0, %1;" : "=f"(r) : "f"(x)); return r; }
__device__ __forceinline__ float silu_mul(float g, float u) { float hg = 0.5f * g; float a = hg * u; return fmaf(a, tanh_a(hg), a); }
__device__ __forceinline__ void stsm4(uint32_t addr, uint32_t r0, uint32_t r1, uint32_t r2, uint32_t r3) {
  asm volatile("stmatrix.sync.aligned.m8n8.x4.shared.b16 [%0], {%1, %2, %3, %4};" ::"r"(addr), "r"(r0), "r"(r1), "r"(r2), "r"(r3) : "memory");
}
__device__ __forceinline__ void mma16816(float (&c)[4], uint32_t a0, uint32_t a1, uint32_t a2, uint32_t a3, uint32_t b0, uint32_t b1) {
  asm volatile("mma.sync.aligned.m16n8k16.row.col.f32.bf16.bf16.f32 {%0,%1,%2,%3}, {%4,%5,%6,%7}, {%8,%9}, {%0,%1,%2,%3};"
               : "+f"(c[0]), "+f"(c[1]), "+f"(c[2]), "+f"(c[3]) : "r"(a0), "r"(a1), "r"(a2), "r"(a3), "r"(b0), "r"(b1));
}
__device__ __forceinline__ uint32_t lds32(uint32_t a) { uint32_t v; asm volatile("ld.shared.u32 %0, [%1];" : "=r"(v) : "r"(a) : "memory"); return v; }
__device__ __forceinline__ void sts32(uint32_t a, uint32_t v) { asm volatile("st.shared.u32 [%0], %1;" ::"r"(a), "r"(v) : "memory"); }
__device__ __forceinline__ void sts16(uint32_t a, unsigned short v) { asm volatile("st.shared.u16 [%0], %1;" ::"r"(a), "h"(v) : "memory"); }
__device__ __forceinline__ void sts64f(uint32_t a, float x, float y) { asm volatile("st.shared.v2.f32 [%0], {%1, %2};" ::"r"(a), "f"(x), "f"(y) : "memory"); }
__device__ __forceinline__ void sts128(uint32_t a, uint4 v) { asm volatile("st.shared.v4.u32 [%0], {%1,%2,%3,%4};" ::"r"(a), "r"(v.x), "r"(v.y), "r"(v.z), "r"(v.w) : "memory"); }
__device__ __forceinline__ float4 lds128f(uint32_t a) { float4 v; asm volatile("ld.shared.v4.f32 {%0,%1,%2,%3}, [%4];" : "=f"(v.x), "=f"(v.y), "=f"(v.z), "=f"(v.w) : "r"(a) : "memory"); return v; }
__device__ __forceinline__ void st_async4(uint32_t raddr, float a, float b, float c, float d, uint32_t rbar) {
  asm volatile("st.async.weak.shared::cluster.mbarrier::complete_tx::bytes.v4.f32 [%0], {%1,%2,%3,%4}, [%5];" ::"r"(raddr), "f"(a), "f"(b), "f"(c), "f"(d), "r"(rbar) : "memory");
}
__device__ __forceinline__ uint4 ldg128(const void* p) { uint4 v; asm volatile("ld.global.nc.L1::no_allocate.v4.u32 {%0,%1,%2,%3}, [%4];" : "=r"(v.x), "=r"(v.y), "=r"(v.z), "=r"(v.w) : "l"(p)); return v; }

constexpr float LOG2E = 1.4426950408889634f;

__device__ __forceinline__ uint32_t mbar_test(uint32_t bar, uint32_t parity) {
  uint32_t ok;
  asm volatile("{\n.reg .pred p;\nmbarrier.test_wait.parity.shared::cta.b64 p, [%1], %2;\nselp.u32 %0, 1, 0, p;\n}\n" : "=r"(ok) : "r"(bar), "r"(parity) : "memory");
  return ok;
}
__device__ __forceinline__ void st_async4u(uint32_t raddr, uint4 v, uint32_t rbar) {
  asm volatile("st.async.weak.shared::cluster.mbarrier::complete_tx::bytes.v4.b32 [%0], {%1,%2,%3,%4}, [%5];" ::"r"(raddr), "r"(v.x), "r"(v.y), "r"(v.z), "r"(v.w), "r"(rbar) : "memory");
}
#define KEEPF(x) asm volatile("" ::"f"(x))

__device__ __forceinline__ void hh_both(const float (&p)[8], uint32_t (&ph)[8]) {
  const float* p0 = p; const float* p1 = p + 4;
  float mx[2], mn[2];
#pragma unroll
  for (int i = 0; i < 2; i++) {
    mx[i] = fmaxf(fmaxf(p0[2 * i], p0[2 * i + 1]), fmaxf(p1[2 * i], p1[2 * i + 1]));
    mn[i] = fminf(fminf(p0[2 * i], p0[2 * i + 1]), fminf(p1[2 * i], p1[2 * i + 1]));
  }
#pragma unroll
  for (int o = 1; o <= 2; o <<= 1) {
#pragma unroll
    for (int i = 0; i < 2; i++) {
      mx[i] = fmaxf(mx[i], __shfl_xor_sync(0xffffffffu, mx[i], o));
      mn[i] = fminf(mn[i], __shfl_xor_sync(0xffffffffu, mn[i], o));
    }
  }
  float e[2][4], f[2][4], sp[2], sn[2];
#pragma unroll
  for (int i = 0; i < 2; i++) {
    float mxl = -mx[i] * LOG2E, mnl = mn[i] * LOG2E;
    float v[4] = {p0[2 * i], p0[2 * i + 1], p1[2 * i], p1[2 * i + 1]};
#pragma unroll
    for (int c = 0; c < 4; c++) { e[i][c] = ex2(fmaf(v[c], LOG2E, mxl)); f[i][c] = ex2(fmaf(v[c], -LOG2E, mnl)); }
    sp[i] = (e[i][0] + e[i][1]) + (e[i][2] + e[i][3]);
    sn[i] = (f[i][0] + f[i][1]) + (f[i][2] + f[i][3]);
  }
#pragma unroll
  for (int o = 1; o <= 2; o <<= 1) {
#pragma unroll
    for (int i = 0; i < 2; i++) {
      sp[i] += __shfl_xor_sync(0xffffffffu, sp[i], o);
      sn[i] += __shfl_xor_sync(0xffffffffu, sn[i], o);
    }
  }
#pragma unroll
  for (int i = 0; i < 2; i++) {
    float rp = rcp(sp[i]), rn = rcp(sn[i]);
    ph[0 + i] = pack_bf16(e[i][0] * rp, e[i][1] * rp);
    ph[2 + i] = pack_bf16(e[i][2] * rp, e[i][3] * rp);
    ph[4 + i] = pack_bf16(f[i][0] * rn, f[i][1] * rn);
    ph[6 + i] = pack_bf16(f[i][2] * rn, f[i][3] * rn);
  }
}

template <int TA, int TB, int NK, int FIRST>
__device__ __forceinline__ void p2_issue(float (&acc)[64], uint32_t sb, uint32_t bar0, uint32_t aoff) {
  uint32_t aaddr = aoff;
  if (TA >= 0) {
    mbar_wait(bar0 + 8u * (B_FULLT + (TA < 0 ? 0 : TA)), 0);
    aaddr = sb + slot2_off(tile_slot(TA < 0 ? 0 : TA)) + aoff;
  }
  mbar_wait(bar0 + 8u * (B_FULLT + TB), 0);
  uint64_t dA = mkdesc(aaddr, 128, 256, 0), dB = mkdesc(sb + slot2_off(tile_slot(TB)), 8192, 1024, 1);
  wg_fence();
  wgmma_n128(acc, dA, dB, FIRST ? 0 : 1);
  wgmma_n128(acc, dA + 128, dB + 128, 1);
  wgmma_n128(acc, dA + 256, dB + 256, 1);
  if (NK > 3) wgmma_n128(acc, dA + 384, dB + 384, 1);
}
template <int TA, int TB, int NK, int FIRST, int RA, int RB, int WAITPREV>
__device__ __forceinline__ void p2_step(float (&acc)[64], uint32_t sb, uint32_t bar0, uint32_t aoff, int lane) {
  p2_issue<TA, TB, NK, FIRST>(acc, sb, bar0, aoff);
  wg_commit();
  if (WAITPREV) {
    wg_wait<1>();
    if (lane == 0) {
      if (RA >= 0) mbar_arrive(bar0 + 8u * (B_EMPTYT + (RA < 0 ? 0 : RA)));
      if (RB >= 0) mbar_arrive(bar0 + 8u * (B_EMPTYT + (RB < 0 ? 0 : RB)));
    }
  }
}

__device__ __forceinline__ void pass_n128(float (&a0)[64], float (&a1)[64], int s0, bool xf, uint32_t sb, uint32_t bar0, int lane) {
  const uint64_t dA0 = mkdesc(sb + OFF_XN, 16, 1024, 1);
#pragma unroll 1
  for (int c = 0; c < 8; c++) {
    const int s = s0 + c;
    mbar_wait(bar0 + 8u * (B_FULL1 + (s & 15)), s >> 4);
    const uint64_t dB = mkdesc(sb + OFF_R + (uint32_t)(c & 3) * 16384u, 8192, 1024, 1);
    const uint64_t dA = dA0 + (uint64_t)(c * 1024);
    wg_fence();
#pragma unroll
    for (int k = 0; k < 4; k++) {
      wgmma_n128(a0, dA + 2 * k, dB + 128 * k, (c > 0 || k > 0) ? 1 : 0);
      wgmma_n128(a1, dA + 512 + 2 * k, dB + 128 * k, (c > 0 || k > 0) ? 1 : 0);
    }
    wg_commit();
    if (c > 0) {
      wg_wait<1>();
      if (lane == 0) {
        mbar_arrive(bar0 + 8u * (B_EMPTY1 + ((s - 1) & 15)));
        if (xf && c <= 6) mbar_arrive(bar0 + 8u * (B_XF + c - 1));
      }
    }
  }
  wg_wait<0>();
  if (lane == 0) mbar_arrive(bar0 + 8u * (B_EMPTY1 + ((s0 + 7) & 15)));
}

__device__ __forceinline__ void teardown(bool leader) {
  if (leader) {
    unsigned int tk = atomicAdd(&g_done, 1u);
    if ((tk & 127u) == 127u) { atomicAdd(&g_epoch, 1u); }
  }
}

__global__ void __cluster_dims__(2, 1, 1) __launch_bounds__(384, 1)
fused_kernel(const __grid_constant__ TMaps tm, const __nv_bfloat16* __restrict__ x, const __nv_bfloat16* __restrict__ wphi,
             __nv_bfloat16* __restrict__ out) {
  extern __shared__ __align__(1024) unsigned char smem_raw[];
  const uint32_t sb = smem_u32(smem_raw);
  const int tid = threadIdx.x;
  const int warp = tid >> 5, lane = tid & 31;
  const int bid = blockIdx.x;
  const int m = bid >> 3, r = bid & 7, nq = r >> 1, kh = r & 1;
  const int sl = kh * 4 + nq;
  const int f0 = kh * 688 + nq * 176;
  const uint32_t bar0 = sb + OFF_BAR;
  auto BAR = [&](int i) { return bar0 + 8u * (uint32_t)i; };

  if (tid == 128) asm volatile("st.shared.u64 [%0 + 1016], %1;" ::"r"(bar0), "l"(gtime() + 2000000ull) : "memory");
  if (tid < NBAR) {
    int cnt = 1;
    if (tid >= B_EMPTY1 && tid < B_EMPTY1 + 16) cnt = 4;
    else if (tid >= B_EMPTYT && tid < B_EMPTYT + 19) cnt = 8;
    else if (tid >= B_KV && tid <= B_O) cnt = 128;
    else if (tid == B_KVB || tid == B_WPHI) cnt = 32;
    else if (tid == B_XO_OK || tid == B_XS_OK || tid == B_XLAND) cnt = 8;
    else if (tid == B_XNL) cnt = 256;
    else if (tid >= B_STGFREE && tid < B_HCRD) cnt = 4;
    mbar_init(BAR(tid), cnt);
    if (tid == B_XNR) mbar_expect_tx(BAR(B_XNR), 65536);
    if (tid >= B_XO_FULL && tid < B_XO_FULL + 4) mbar_expect_tx(BAR(tid), 16384);
    asm volatile("fence.mbarrier_init.release.cluster;" ::: "memory");
  }
  __syncthreads();
  asm volatile("barrier.cluster.arrive.relaxed.aligned;" ::: "memory");

  if (warp >= 8) {
    asm volatile("setmaxnreg.dec.sync.aligned.u32 40;");
    asm volatile("barrier.cluster.wait.aligned;" ::: "memory");
    if (warp == 8) {
      if (lane == 0) {
        MARK(0);
        mbar_wait(BAR(B_XLAND), 0);
#pragma unroll 1
        for (int s = 0; s < 32; s++) {
          const int dp = c_stage_dep[s];
          if (dp >= 0) mbar_wait(BAR(B_EMPTY1 + (dp & 15)), dp >> 4);
          const uint32_t fb = BAR(B_FULL1 + (s & 15));
          const int row = (s & 7) * 64, ps = s >> 3;
          const int u0 = stage_unit0(s);
          const uint32_t rb = sb + OFF_R;
          if (ps == 0) {
            mbar_expect_tx(fb, 16384);
            tma3d(rb + (uint32_t)(u0 & 7) * 8192u, &tm.kv, sl * 64, row, 1, fb);
          } else if (ps == 1) {
            mbar_expect_tx(fb, 24576);
            tma2d(rb + (uint32_t)(u0 & 7) * 8192u, &tm.q, sl * 64, row, fb);
            tma2d(rb + (uint32_t)((u0 + 1) & 7) * 8192u, &tm.w1, f0 + 128, row, fb);
            tma2d(rb + (uint32_t)((u0 + 2) & 7) * 8192u, &tm.w3, f0 + 128, row, fb);
          } else {
            mbar_expect_tx(fb, 16384);
            tma2d(rb + (uint32_t)(u0 & 7) * 8192u, &tm.w1, f0 + (ps - 2) * 64, row, fb);
            tma2d(rb + (uint32_t)(u0 & 7) * 8192u + 8192u, &tm.w3, f0 + (ps - 2) * 64, row, fb);
          }
        }
        MARK(2);
        const int colk = nq * 128 + kh * 64, cols = nq * 128 + (kh ^ 1) * 64;
#pragma unroll 1
        for (int n = 0; n < 16; n++) {
          const int grp = n >> 2, d = n & 3;
          const int t = grp * 7 + 2 * d;
          const int slot = c_tile_slot[t], pv = c_tile_prev[t];
          if (pv >= 0) mbar_wait(BAR(B_EMPTYT + pv), 0);
          else if (slot < 6 && t < 9) mbar_wait(BAR(B_XF + slot), 0);
          else if (slot >= 7) mbar_wait(BAR(B_EMPTY1 + 12 + (slot - 7)), 1);
          if (t == 9) mbar_wait(BAR(B_HCRD), 0);
          if (t == 18) mbar_wait(BAR(B_O), 0);
          if (t == 25) mbar_wait(BAR(B_HBRD), 0);
          const int q = (nq + d) & 3;
          const CUtensorMap* mp = grp == 3 ? &tm.wo : (grp == 0 ? &tm.w2t : &tm.w2);
          const int row = grp == 3 ? (kh * 4 + q) * 64 : kh * 688 + q * 176 + (grp == 0 ? 128 : (grp - 1) * 64);
          const uint32_t dst = sb + slot2_off(slot), fb = BAR(B_FULLT + t);
          mbar_expect_tx(fb, grp == 0 ? 12288u : 16384u);
          tma2d(dst, mp, colk, row, fb);
          tma2d(dst + 8192, mp, cols, row, fb);
        }
        MARK(5);
      }
    } else if (warp == 9) {
      if (lane == 0) {
        const unsigned int epoch = *(volatile unsigned int*)&g_epoch;
        const int id = m * 8 + sl;
#pragma unroll 1
        for (int job = 0; job < 5; job++) {
          mbar_wait(BAR(B_KV + job), 0);
          unsigned int* fl;
          if (job == 0) {
            bulk_red_add_f32(&g_kv[epoch & 1][sl * 2048], sb + OFF_HA, 8192);
            bulk_red_add_f32(&g_z[epoch & 1][sl * 128], sb + OFF_HA + 8192, 512);
            fl = g_kvcnt + sl * 8;
          } else if (job == 1) {
            bulk_s2g(g_hc + (size_t)id * 12288, sb + OFF_HC, 12288);
            fl = g_flag_hc + id * 8;
          } else {
            bulk_s2g((job == 2 ? g_ha : (job == 3 ? g_hb : g_o)) + (size_t)id * 16384, sb + (job == 2 ? OFF_HA : (job == 3 ? OFF_HB : OFF_OO)), 16384);
            fl = (job == 2 ? g_flag_ha : (job == 3 ? g_flag_hb : g_flag_o)) + id * 8;
          }
          bulk_commit(); bulk_wait0();
          red_release_gpu(fl, 1);
          if (job == 0) mbar_arrive(BAR(B_KVDONE));
          if (job == 1) mbar_arrive(BAR(B_HCRD));
          if (job == 2) mbar_arrive(BAR(B_HARD));
          if (job == 3) mbar_arrive(BAR(B_HBRD));
          MARK(1 + job);
        }
      }
    } else if (warp == 11) {
      {
        sts32(sb + OFF_ONES + lane * 4, 0x3F803F80u);
        const unsigned short* wp = reinterpret_cast<const unsigned short*>(wphi) + sl * 4 * 256;
#pragma unroll 4
        for (int i = lane; i < 1024; i += 32) {
          int h = i >> 8, d = (i >> 4) & 15, f = i & 15;
          sts16(sb + OFF_WPHI + h * 512 + (f >> 3) * 256 + (d >> 3) * 128 + (f & 7) * 16 + (d & 7) * 2, wp[i]);
        }
        fence_async_smem();
        mbar_arrive(BAR(B_WPHI));
      }
      const unsigned int epoch = *(volatile unsigned int*)&g_epoch;
      reinterpret_cast<float4*>(&g_kv[(epoch + 1) & 1][bid * 128])[lane] = make_float4(0.f, 0.f, 0.f, 0.f);
      if (lane < 8) g_z[(epoch + 1) & 1][bid * 8 + lane] = 0.f;
      if (lane == 0) {
        const int row = (m >> 1) * 64;
        mbar_wait(BAR(B_XLAND), 0);
        if (m & 1) { pf3d(&tm.kv, sl * 64, row, 1); pf2d(&tm.q, sl * 64, row); }
        else { pf2d(&tm.w1, f0 + 128, row); pf2d(&tm.w3, f0 + 128, row); }
        __nanosleep(800);
        pf2d(&tm.w1, f0 + (m & 1) * 64, row); pf2d(&tm.w3, f0 + (m & 1) * 64, row);
        __nanosleep(800);
#pragma unroll 1
        for (int i = bid; i < 240; i += 128) {
          if (i < 176) pf2d(&tm.w2, (i & 7) * 64, (i >> 3) * 64);
          else pf2d(&tm.wo, (i & 7) * 64, ((i - 176) >> 3) * 64);
        }
      }
      __syncwarp();
      const int grp = lane / 3, d = lane - grp * 3 + 1;
      const int id = m * 8 + kh * 4 + ((nq + d) & 3);
      int tile = lane < 12 ? grp * 7 + 2 * d - 1 : 10;
      const unsigned char* src = grp == 0 ? g_hc + (size_t)id * 12288 : (grp == 1 ? g_ha : (grp == 2 ? g_hb : g_o)) + (size_t)id * 16384;
      const unsigned int* flag = (grp == 0 ? g_flag_hc : (grp == 1 ? g_flag_ha : (grp == 2 ? g_flag_hb : g_flag_o))) + id * 8;
      unsigned int tgt = epoch + 1u;
      if (lane == 12) { flag = g_kvcnt + sl * 8; tgt = 16u * (epoch + 1u); }
      const int pv = c_tile_prev[tile], slot = c_tile_slot[tile];
      uint32_t wb = pv >= 0 ? BAR(B_EMPTYT + pv) : (slot < 6 ? BAR(B_XF + slot) : BAR(B_HB));
      if (lane == 12) wb = BAR(B_XF + 0);
      int state = lane <= 12 ? 0 : 2;
      while (true) {
        if (state == 0 && (int)(ld_acquire_gpu(flag) - tgt) >= 0) state = 1;
        const bool go = state == 1 && mbar_test(wb, 0) && (tile != 17 || mbar_test(BAR(B_HARD), 0));
        if (go && lane < 12) {
          uint32_t bytes = grp == 0 ? 12288u : 16384u;
          uint32_t fb = BAR(B_FULLT + tile);
          mbar_expect_tx(fb, bytes);
          bulk_g2s(sb + slot2_off(slot), src, bytes, fb);
          state = 2;
        }
        if (__ballot_sync(0xffffffffu, go && lane == 12)) {
          MARK(1);
          if (lane == 0) {
            mbar_expect_tx(BAR(B_KVRAW), 8704);
            bulk_g2s(sb + OFF_KVRAW, &g_kv[epoch & 1][sl * 2048], 8192, BAR(B_KVRAW));
            bulk_g2s(sb + OFF_KVRAW + 8192, &g_z[epoch & 1][sl * 128], 512, BAR(B_KVRAW));
          }
          mbar_wait(BAR(B_KVRAW), 0);
#pragma unroll 2
          for (int i = lane; i < 256; i += 32) {
            float4 v0 = lds128f(sb + OFF_KVRAW + i * 32), v1 = lds128f(sb + OFF_KVRAW + i * 32 + 16);
            int h = i >> 6, dd = (i >> 2) & 15, fo = i & 3;
            uint4 w; w.x = pack_bf16(v0.x, v0.y); w.y = pack_bf16(v0.z, v0.w); w.z = pack_bf16(v1.x, v1.y); w.w = pack_bf16(v1.z, v1.w);
            sts128(sb + OFF_KVB + h * 1536 + (fo >> 1) * 768 + (dd >> 3) * 256 + (fo & 1) * 128 + (dd & 7) * 16, w);
          }
          {
            const int h = lane >> 3, fo = (lane >> 1) & 3, half = lane & 1;
            float4 v0 = lds128f(sb + OFF_KVRAW + 8192 + h * 128 + fo * 32), v1 = lds128f(sb + OFF_KVRAW + 8192 + h * 128 + fo * 32 + 16);
            uint4 zz; zz.x = pack_bf16(v0.x, v0.y); zz.y = pack_bf16(v0.z, v0.w); zz.z = pack_bf16(v1.x, v1.y); zz.w = pack_bf16(v1.z, v1.w);
            uint32_t a = sb + OFF_KVB + h * 1536 + (fo >> 1) * 768 + 512 + (fo & 1) * 128 + half * 64;
            sts128(a, zz); sts128(a + 16, zz); sts128(a + 32, zz); sts128(a + 48, zz);
          }
          fence_async_smem();
          mbar_arrive(BAR(B_KVB));
          if (lane == 12) state = 2;
          MARK(3);
        }
        if (__all_sync(0xffffffffu, state == 2)) break;
        unsigned long long dl; asm volatile("ld.shared.u64 %0, [%1 + 1016];" : "=l"(dl) : "r"(bar0) : "memory");
        if (gtime() >= dl) break;
        __nanosleep(64);
      }
      MARK(2);
    }
  } else {
    asm volatile("setmaxnreg.inc.sync.aligned.u32 232;");
    MARK(0);
    const int wg = warp >> 2, w4 = warp & 3;
    const int g = lane >> 2, t4 = lane & 3;
    const int tw = tid & 127;
    const uint32_t peer = (uint32_t)(kh ^ 1);
    {
      const int rsub = lane >> 3, sub = lane & 7;
      uint4 v[8], vn[8];
      const int row0 = kh * 64 + warp * 8 + rsub;
      const __nv_bfloat16* xb = x + (size_t)(m * 128 + row0) * D_ + sub * 8;
#pragma unroll
      for (int i = 0; i < 8; i++) v[i] = ldg128(xb + i * 64);
#pragma unroll
      for (int i = 0; i < 8; i++) vn[i] = ldg128(xb + 4 * D_ + i * 64);
      asm volatile("barrier.cluster.wait.aligned;" ::: "memory");
      const uint32_t rbar = mapa(BAR(B_XNR), peer);
      const uint32_t rsb = mapa(sb, peer);
#pragma unroll 1
      for (int gi = 0; gi < 2; gi++) {
        float s = 0.f;
#pragma unroll
        for (int i = 0; i < 8; i++) {
          s += (bf_lo(v[i].x) + bf_hi(v[i].x)) + (bf_lo(v[i].y) + bf_hi(v[i].y));
          s += (bf_lo(v[i].z) + bf_hi(v[i].z)) + (bf_lo(v[i].w) + bf_hi(v[i].w));
        }
        s += __shfl_xor_sync(0xffffffffu, s, 1);
        s += __shfl_xor_sync(0xffffffffu, s, 2);
        s += __shfl_xor_sync(0xffffffffu, s, 4);
        if (gi == 0 && lane == 0) mbar_arrive(BAR(B_XLAND));
        MARK(16 + gi);
        const float mean = s * (1.f / 512.f);
        float q0 = 0.f, q1 = 0.f;
#pragma unroll
        for (int i = 0; i < 8; i++) {
          const uint32_t* w = reinterpret_cast<const uint32_t*>(&v[i]);
#pragma unroll
          for (int e = 0; e < 4; e++) {
            float d0 = bf_lo(w[e]) - mean, d1 = bf_hi(w[e]) - mean;
            q0 = fmaf(d0, d0, q0); q1 = fmaf(d1, d1, q1);
          }
        }
        float q = q0 + q1;
        q += __shfl_xor_sync(0xffffffffu, q, 1);
        q += __shfl_xor_sync(0xffffffffu, q, 2);
        q += __shfl_xor_sync(0xffffffffu, q, 4);
        const float rstd = rsqrtf(q * (1.f / 512.f) + 1e-5f);
        const float nb = -mean * rstd;
        const int row = row0 + gi * 4;
        const uint32_t ro = OFF_XN + row * 128 + ((sub ^ (row & 7)) << 4);
#pragma unroll
        for (int i = 0; i < 8; i++) {
          const uint32_t* w = reinterpret_cast<const uint32_t*>(&v[i]);
          uint4 o;
          o.x = pack_bf16(fmaf(bf_lo(w[0]), rstd, nb), fmaf(bf_hi(w[0]), rstd, nb));
          o.y = pack_bf16(fmaf(bf_lo(w[1]), rstd, nb), fmaf(bf_hi(w[1]), rstd, nb));
          o.z = pack_bf16(fmaf(bf_lo(w[2]), rstd, nb), fmaf(bf_hi(w[2]), rstd, nb));
          o.w = pack_bf16(fmaf(bf_lo(w[3]), rstd, nb), fmaf(bf_hi(w[3]), rstd, nb));
          st_async4u(rsb + ro + i * 16384, o, rbar);
          sts128(sb + ro + i * 16384, o);
          v[i] = vn[i];
        }
      }
      fence_async_smem();
      mbar_arrive(BAR(B_XNL));
      mbar_wait(BAR(B_XNL), 0);
      mbar_wait_cluster(BAR(B_XNR), 0);
      fence_async_smem();
    }
    MARK(1);
    const uint32_t st_off = (uint32_t)((2 * w4 + ((lane >> 3) & 1)) * 256 + (lane >> 4) * 128 + (lane & 7) * 16);

    uint32_t ph[64];
    {
      uint32_t xp[32], vp[32];
      if (wg == 0) {
        float a0[64], a1[64];
        pass_n128(a0, a1, 0, false, sb, bar0, lane);
#pragma unroll
        for (int i = 0; i < 16; i++) {
          xp[i] = pack_bf16(a0[2 * i], a0[2 * i + 1]);        xp[16 + i] = pack_bf16(a1[2 * i], a1[2 * i + 1]);
          vp[i] = pack_bf16(a0[32 + 2 * i], a0[33 + 2 * i]);  vp[16 + i] = pack_bf16(a1[32 + 2 * i], a1[33 + 2 * i]);
        }
      } else {
        float aq[2][32], ag[2][24], au[2][24];
        const uint64_t dA0 = mkdesc(sb + OFF_XN, 16, 1024, 1);
        const uint64_t dR = mkdesc(sb + OFF_R, 8192, 1024, 1);
        int u = 0;
#pragma unroll 1
        for (int c = 0; c < 8; c++) {
          mbar_wait(BAR(B_FULL1 + 8 + c), 0);
          const uint64_t dQ = dR + (uint64_t)(u * 512), dG = dR + (uint64_t)(((u + 1) & 7) * 512), dU = dR + (uint64_t)(((u + 2) & 7) * 512);
          const uint64_t dA = dA0 + (uint64_t)(c * 1024);
          wg_fence();
#pragma unroll
          for (int k = 0; k < 4; k++) {
            const int sc = (c > 0 || k > 0) ? 1 : 0;
#pragma unroll
            for (int mt = 0; mt < 2; mt++) {
              wgmma_n64(aq[mt], dA + 512 * mt + 2 * k, dQ + 128 * k, sc);
              wgmma_n48(ag[mt], dA + 512 * mt + 2 * k, dG + 128 * k, sc);
              wgmma_n48(au[mt], dA + 512 * mt + 2 * k, dU + 128 * k, sc);
            }
          }
          wg_commit();
          if (c > 0) { wg_wait<1>(); if (lane == 0) mbar_arrive(BAR(B_EMPTY1 + 8 + c - 1)); }
          u = (u + 3) & 7;
        }
        wg_wait<0>();
        if (lane == 0) mbar_arrive(BAR(B_EMPTY1 + 15));
#pragma unroll
        for (int i = 0; i < 16; i++) {
          xp[i] = pack_bf16(aq[0][2 * i], aq[0][2 * i + 1]);  xp[16 + i] = pack_bf16(aq[1][2 * i], aq[1][2 * i + 1]);
          vp[i] = 0u; vp[16 + i] = 0u;
        }
        uint32_t rr[24];
#pragma unroll
        for (int mt = 0; mt < 2; mt++)
#pragma unroll
          for (int e = 0; e < 12; e++) {
            rr[mt * 12 + e] = pack_bf16(silu_mul(ag[mt][2 * e], au[mt][2 * e]), silu_mul(ag[mt][2 * e + 1], au[mt][2 * e + 1]));
            if (e >= 8 && nq == 3) rr[mt * 12 + e] = 0u;
          }
        mbar_wait(BAR(B_STGFREE), 0);
#pragma unroll
        for (int mt = 0; mt < 2; mt++)
#pragma unroll
          for (int kb = 0; kb < 3; kb++)
            stsm4(sb + OFF_HC + mt * 6144 + kb * 2048 + st_off, rr[mt * 12 + 4 * kb], rr[mt * 12 + 4 * kb + 1], rr[mt * 12 + 4 * kb + 2], rr[mt * 12 + 4 * kb + 3]);
        fence_async_smem();
        mbar_arrive(BAR(B_HC));
      }
      MARK(2);
      {
        float p[8][8];
        const uint64_t dWP = mkdesc(sb + OFF_WPHI, 128, 256, 0);
        mbar_wait(BAR(B_WPHI), 0);
        wg_fence();
#pragma unroll
        for (int i = 0; i < 8; i++) wgmma_rs_n16(p[i], xp[4 * i], xp[4 * i + 1], xp[4 * i + 2], xp[4 * i + 3], dWP + (i & 3) * 32, 0);
        wg_commit();
        wg_wait<0>();
#pragma unroll 1
        for (int it = 0; it < 4; it++) {
          uint32_t r0[8], r1[8];
          hh_both(p[0], r0);
          hh_both(p[1], r1);
#pragma unroll
          for (int i = 0; i < 6; i++)
#pragma unroll
            for (int e = 0; e < 8; e++) { p[i][e] = p[i + 2][e]; ph[i * 8 + e] = ph[(i + 2) * 8 + e]; }
#pragma unroll
          for (int e = 0; e < 8; e++) { ph[48 + e] = r0[e]; ph[56 + e] = r1[e]; }
        }
      }
      MARK(3);
      if (wg == 0) {
        const uint32_t so = (uint32_t)((2 * w4 + ((lane >> 3) & 1)) * 128 + (lane >> 4) * 2048 + (lane & 7) * 16);
        const uint64_t dPK = mkdesc(sb + OFF_HA, 128, 2048, 0), dV = mkdesc(sb + OFF_HC, 128, 2048, 0), dOne = mkdesc(sb + OFF_ONES, 0, 0, 0);
        float keep[2][8], keepz[2][2];
#pragma unroll
        for (int pr = 0; pr < 2; pr++) {
#pragma unroll
          for (int mt = 0; mt < 2; mt++)
#pragma unroll
            for (int hh = 0; hh < 2; hh++) {
              const int ti = (mt * 4 + pr * 2 + hh) * 8, vi = mt * 16 + (pr * 2 + hh) * 4;
              stsm4(sb + OFF_HA + so + mt * 1024 + hh * 8192, ph[ti], ph[ti + 1], ph[ti + 2], ph[ti + 3]);
              stsm4(sb + OFF_HA + so + mt * 1024 + hh * 8192 + 4096, ph[ti + 4], ph[ti + 5], ph[ti + 6], ph[ti + 7]);
              stsm4(sb + OFF_HC + so + mt * 1024 + hh * 4096, vp[vi], vp[vi + 1], vp[vi + 2], vp[vi + 3]);
            }
          fence_async_smem();
          named_bar(1, 128);
          float dkv[16], dz[4];
          wg_fence();
#pragma unroll
          for (int ks = 0; ks < 8; ks++) {
            wgmma_n32_tt(dkv, dPK + ks * 16, dV + ks * 16, ks > 0);
            wgmma_n8_tt(dz, dPK + ks * 16, dOne, ks > 0);
          }
          wg_commit();
          wg_wait<0>();
#pragma unroll
          for (int e = 0; e < 8; e++) keep[pr][e] = (w4 >= 2) ? dkv[8 + e] : dkv[e];
          keepz[pr][0] = 0.5f * (dz[0] + dz[1]); keepz[pr][1] = 0.5f * (dz[2] + dz[3]);
          named_bar(1, 128);
        }
        if (lane == 0) mbar_arrive(BAR(B_STGFREE));
#pragma unroll
        for (int p = 0; p < 2; p++) {
          const int h = p * 2 + (w4 >> 1), f = (w4 & 1) * 16 + g;
          uint32_t a = sb + OFF_HA + h * 2048 + t4 * 256 + f * 4;
          sts32(a, __float_as_uint(keep[p][0]));              sts32(a + 128, __float_as_uint(keep[p][1]));
          sts32(a + 32, __float_as_uint(keep[p][2]));         sts32(a + 128 + 32, __float_as_uint(keep[p][3]));
          sts32(a + 1024, __float_as_uint(keep[p][4]));       sts32(a + 1024 + 128, __float_as_uint(keep[p][5]));
          sts32(a + 1024 + 32, __float_as_uint(keep[p][6]));  sts32(a + 1024 + 128 + 32, __float_as_uint(keep[p][7]));
          if (t4 == 0) {
            sts32(sb + OFF_HA + 8192 + h * 128 + f * 4, __float_as_uint(keepz[p][0]));
            sts32(sb + OFF_HA + 8192 + h * 128 + (f + 8) * 4, __float_as_uint(keepz[p][1]));
          }
        }
        fence_async_smem();
        mbar_arrive(BAR(B_KV));
      }
    }
    MARK(4);
    {
      float a0[64], a1[64];
      pass_n128(a0, a1, 16 + 8 * wg, wg == 1, sb, bar0, lane);
      MARK(5);
      uint32_t rr[32];
#pragma unroll
      for (int e = 0; e < 16; e++) {
        rr[e] = pack_bf16(silu_mul(a0[2 * e], a0[32 + 2 * e]), silu_mul(a0[2 * e + 1], a0[33 + 2 * e]));
        rr[16 + e] = pack_bf16(silu_mul(a1[2 * e], a1[32 + 2 * e]), silu_mul(a1[2 * e + 1], a1[33 + 2 * e]));
      }
      if (wg == 0) mbar_wait(BAR(B_KVDONE), 0); else named_bar(2, 128);
      const uint32_t hb = sb + (wg == 0 ? OFF_HA : OFF_HB) + st_off;
#pragma unroll
      for (int i = 0; i < 8; i++) stsm4(hb + i * 2048, rr[4 * i], rr[4 * i + 1], rr[4 * i + 2], rr[4 * i + 3]);
      fence_async_smem();
      mbar_arrive(BAR(B_HA + wg));
    }
    MARK(6);
    if (wg == 1) {
      float nd[8][12];
      const uint64_t dKV = mkdesc(sb + OFF_KVB, 128, 256, 0);
      mbar_wait(BAR(B_KVB), 0);
      wg_fence();
#pragma unroll
      for (int i = 0; i < 8; i++) {
        wgmma_rs_n24(nd[i], ph[8 * i], ph[8 * i + 1], ph[8 * i + 2], ph[8 * i + 3], dKV + (i & 3) * 96, 0);
        wgmma_rs_n24(nd[i], ph[8 * i + 4], ph[8 * i + 5], ph[8 * i + 6], ph[8 * i + 7], dKV + (i & 3) * 96 + 48, 1);
      }
      wg_commit();
      wg_wait<0>();
#pragma unroll
      for (int i = 0; i < 8; i++) {
        float r0 = rcp(0.5f * (nd[i][8] + nd[i][9]) + 1e-6f), r1 = rcp(0.5f * (nd[i][10] + nd[i][11]) + 1e-6f);
        stsm4(sb + OFF_OO + st_off + i * 2048, pack_bf16(nd[i][0] * r0, nd[i][1] * r0), pack_bf16(nd[i][2] * r1, nd[i][3] * r1),
              pack_bf16(nd[i][4] * r0, nd[i][5] * r0), pack_bf16(nd[i][6] * r1, nd[i][7] * r1));
      }
      fence_async_smem();
      mbar_arrive(BAR(B_O));
    }
    MARK(7);
    {
      float a_o[64], a_s[64];
      const uint32_t w8 = wg * 8192, w6 = wg * 6144;
      mbar_wait(BAR(B_HC), 0);
      p2_step<-1, 0, 3, 1, -1, -1, 0>(a_o, sb, bar0, sb + OFF_HC + w6, lane);
      p2_step<1, 2, 3, 0, -1, 0, 1>(a_o, sb, bar0, w6, lane);
      p2_step<3, 4, 3, 0, 1, 2, 1>(a_o, sb, bar0, w6, lane);
      p2_step<5, 6, 3, 0, 3, 4, 1>(a_o, sb, bar0, w6, lane);
      MARK(8);
      mbar_wait(BAR(B_HA), 0);
      p2_step<-1, 7, 4, 0, 5, 6, 1>(a_o, sb, bar0, sb + OFF_HA + w8, lane);
      p2_step<8, 9, 4, 0, -1, 7, 1>(a_o, sb, bar0, w8, lane);
      p2_step<10, 11, 4, 0, -1, 9, 1>(a_o, sb, bar0, w8, lane);
      if (lane == 0) mbar_arrive_remote(mapa(BAR(B_XO_OK), peer));
      p2_step<12, 13, 4, 0, 10, 11, 1>(a_o, sb, bar0, w8, lane);
      MARK(9);
      mbar_wait(BAR(B_HB), 0);
      p2_step<-1, 14, 4, 0, 12, 13, 1>(a_o, sb, bar0, sb + OFF_HB + w8, lane);
      p2_step<15, 16, 4, 0, -1, 14, 1>(a_o, sb, bar0, w8, lane);
      p2_step<17, 18, 4, 0, -1, -1, 1>(a_o, sb, bar0, w8, lane);
      if (lane == 0) mbar_arrive_remote(mapa(BAR(B_XS_OK), peer));
      p2_step<19, 20, 4, 0, 17, 18, 1>(a_o, sb, bar0, w8, lane);
      uint32_t xr[16];
      {
        const uint32_t* xp = reinterpret_cast<const uint32_t*>(x + (size_t)(m * 128 + wg * 64 + w4 * 16 + g) * D_ + nq * 128 + kh * 64 + t4 * 2);
#pragma unroll
        for (int j = 0; j < 8; j++) { xr[2 * j] = __ldg(xp + j * 4); xr[2 * j + 1] = __ldg(xp + 8 * (D_ / 2) + j * 4); }
      }
      MARK(10);
      mbar_wait(BAR(B_O), 0);
      p2_step<-1, 21, 4, 1, -1, -1, 1>(a_s, sb, bar0, sb + OFF_OO + w8, lane);
      {
        mbar_wait_cluster(BAR(B_XO_OK), 0);
        uint32_t ra = mapa(sb + OFF_XO_RECV + wg * 16384 + tw * 16, peer), rb = mapa(BAR(B_XO_FULL + wg), peer);
#pragma unroll
        for (int i = 0; i < 8; i++) st_async4(ra + i * 2048, a_o[32 + 4 * i], a_o[33 + 4 * i], a_o[34 + 4 * i], a_o[35 + 4 * i], rb);
      }
      p2_step<22, 23, 4, 0, -1, -1, 0>(a_s, sb, bar0, w8, lane);
      p2_step<24, 25, 4, 0, -1, -1, 0>(a_s, sb, bar0, w8, lane);
      mbar_wait_cluster(BAR(B_XO_FULL + wg), 0);
      float gt[32];
#pragma unroll
      for (int i = 0; i < 8; i++) {
        float4 v = lds128f(sb + OFF_XO_RECV + wg * 16384 + tw * 16 + i * 2048);
        float o0 = a_o[4 * i] + v.x, o1 = a_o[4 * i + 1] + v.y, o2 = a_o[4 * i + 2] + v.z, o3 = a_o[4 * i + 3] + v.w;
        gt[4 * i] = silu_mul(o0, 1.f); gt[4 * i + 1] = silu_mul(o1, 1.f); gt[4 * i + 2] = silu_mul(o2, 1.f); gt[4 * i + 3] = silu_mul(o3, 1.f);
      }
      p2_step<26, 27, 4, 0, -1, -1, 0>(a_s, sb, bar0, w8, lane);
      MARK(11);
      wg_wait<0>();
      MARK(12);
      {
        mbar_wait_cluster(BAR(B_XS_OK), 0);
        uint32_t ra = mapa(sb + OFF_XS_RECV + wg * 16384 + tw * 16, peer), rb = mapa(BAR(B_XS_FULL + wg), peer);
#pragma unroll
        for (int i = 0; i < 8; i++) st_async4(ra + i * 2048, a_s[32 + 4 * i], a_s[33 + 4 * i], a_s[34 + 4 * i], a_s[35 + 4 * i], rb);
      }
      MARK(13);
      mbar_wait_cluster(BAR(B_XS_FULL + wg), 0);
      MARK(14);
      uint32_t* op = reinterpret_cast<uint32_t*>(out + (size_t)(m * 128 + wg * 64 + w4 * 16 + g) * D_ + nq * 128 + kh * 64 + t4 * 2);
#pragma unroll
      for (int i = 0; i < 8; i++) {
        float4 v = lds128f(sb + OFF_XS_RECV + wg * 16384 + tw * 16 + i * 2048);
        float y0 = fmaf(a_s[4 * i] + v.x, gt[4 * i], bf_lo(xr[2 * i]));
        float y1 = fmaf(a_s[4 * i + 1] + v.y, gt[4 * i + 1], bf_hi(xr[2 * i]));
        float y2 = fmaf(a_s[4 * i + 2] + v.z, gt[4 * i + 2], bf_lo(xr[2 * i + 1]));
        float y3 = fmaf(a_s[4 * i + 3] + v.w, gt[4 * i + 3], bf_hi(xr[2 * i + 1]));
        op[i * 4] = pack_bf16(y0, y1);
        op[8 * (D_ / 2) + i * 4] = pack_bf16(y2, y3);
      }
    }
    MARK(15);
    teardown(tid == 0);
  }
}

typedef CUresult (*EncFn)(CUtensorMap*, CUtensorMapDataType, cuuint32_t, void*, const cuuint64_t*, const cuuint64_t*, const cuuint32_t*,
                          const cuuint32_t*, CUtensorMapInterleave, CUtensorMapSwizzle, CUtensorMapL2promotion, CUtensorMapFloatOOBfill);

void enc(EncFn fn, CUtensorMap* tm, const void* base, int rank, const cuuint64_t* gd, const cuuint64_t* gs, const cuuint32_t* bd) {
  cuuint32_t es[3] = {1, 1, 1};
  CUresult rc = fn(tm, CU_TENSOR_MAP_DATA_TYPE_BFLOAT16, (cuuint32_t)rank, const_cast<void*>(base), gd, gs, bd, es, CU_TENSOR_MAP_INTERLEAVE_NONE,
                   CU_TENSOR_MAP_SWIZZLE_128B, CU_TENSOR_MAP_L2_PROMOTION_L2_128B, CU_TENSOR_MAP_FLOAT_OOB_FILL_NONE);
  (void)rc;
}

}

extern "C" void kernel_launch(void* const* d_in, const int* in_sizes, int n_in, void* d_out, int out_size) {
  const __nv_bfloat16* x    = (const __nv_bfloat16*)d_in[0];
  const __nv_bfloat16* wqkv = (const __nv_bfloat16*)d_in[1];
  const __nv_bfloat16* wphi = (const __nv_bfloat16*)d_in[2];
  const __nv_bfloat16* wo   = (const __nv_bfloat16*)d_in[3];
  const __nv_bfloat16* w1   = (const __nv_bfloat16*)d_in[5];
  const __nv_bfloat16* w3   = (const __nv_bfloat16*)d_in[6];
  const __nv_bfloat16* w2   = (const __nv_bfloat16*)d_in[7];

  static EncFn fn = nullptr;
  if (!fn) {
    void* p = nullptr; cudaDriverEntryPointQueryResult qr;
    cudaGetDriverEntryPoint("cuTensorMapEncodeTiled", &p, cudaEnableDefault, &qr);
    fn = (EncFn)p;
    cudaFuncSetAttribute(fused_kernel, cudaFuncAttributeMaxDynamicSharedMemorySize, SMEM_BYTES);
  }
  TMaps tm;
  { cuuint64_t gd[3] = {512, 512, 3}; cuuint64_t gs[2] = {3072, 1024}; cuuint32_t bd[3] = {64, 64, 2};
    enc(fn, &tm.kv, wqkv, 3, gd, gs, bd); }
  { cuuint64_t gd[2] = {1536, 512}; cuuint64_t gs[1] = {3072}; cuuint32_t bd[2] = {64, 64};
    enc(fn, &tm.q, wqkv, 2, gd, gs, bd); }
  { cuuint64_t gd[2] = {F_, 512}; cuuint64_t gs[1] = {F_ * 2}; cuuint32_t bd[2] = {64, 64};
    enc(fn, &tm.w1, w1, 2, gd, gs, bd);  enc(fn, &tm.w3, w3, 2, gd, gs, bd); }
  { cuuint64_t gd[2] = {512, F_}; cuuint64_t gs[1] = {1024}; cuuint32_t bd[2] = {64, 64}; cuuint32_t bd2[2] = {64, 48};
    enc(fn, &tm.w2, w2, 2, gd, gs, bd); enc(fn, &tm.w2t, w2, 2, gd, gs, bd2); }
  { cuuint64_t gd[2] = {512, 512}; cuuint64_t gs[1] = {1024}; cuuint32_t bd[2] = {64, 64};
    enc(fn, &tm.wo, wo, 2, gd, gs, bd); }

  cudaLaunchConfig_t cfg = {};
  cfg.gridDim = dim3(128); cfg.blockDim = dim3(384); cfg.dynamicSmemBytes = SMEM_BYTES; cfg.stream = cudaStreamPerThread;
  cudaLaunchKernelEx(&cfg, fused_kernel, tm, x, wphi, (__nv_bfloat16*)d_out);
}
```

```cpp
#include <cuda_runtime.h>
#include <cuda_bf16.h>
#include <cuda.h>
#include <stdint.h>

__device__ __forceinline__ void wgmma_n72_tt(float (&d)[36], uint64_t da, uint64_t db, int scale_d) {
  asm volatile("{\n.reg .pred p;\nsetp.ne.b32 p, %38, 0;\n"
  "wgmma.mma_async.sync.aligned.m64n72k16.f32.bf16.bf16 {%0, %1, %2, %3, %4, %5, %6, %7, %8, %9, %10, %11, %12, %13, %14, %15, %16, %17, %18, %19, %20, %21, %22, %23, %24, %25, %26, %27, %28, %29, %30, %31, %32, %33, %34, %35}, %36, %37, p, 1, 1, 1, 1;\n}\n"
  : "+f"(d[0]), "+f"(d[1]), "+f"(d[2]), "+f"(d[3]), "+f"(d[4]), "+f"(d[5]), "+f"(d[6]), "+f"(d[7]), "+f"(d[8]), "+f"(d[9]), "+f"(d[10]), "+f"(d[11]), "+f"(d[12]), "+f"(d[13]), "+f"(d[14]), "+f"(d[15]), "+f"(d[16]), "+f"(d[17]), "+f"(d[18]), "+f"(d[19]), "+f"(d[20]), "+f"(d[21]), "+f"(d[22]), "+f"(d[23]), "+f"(d[24]), "+f"(d[25]), "+f"(d[26]), "+f"(d[27]), "+f"(d[28]), "+f"(d[29]), "+f"(d[30]), "+f"(d[31]), "+f"(d[32]), "+f"(d[33]), "+f"(d[34]), "+f"(d[35]) : "l"(da), "l"(db), "r"(scale_d));
}
__device__ __forceinline__ void wgmma_rs_n128(float (&d)[64], uint32_t a0, uint32_t a1, uint32_t a2, uint32_t a3, uint64_t db, int scale_d) {
  asm volatile("{\n.reg .pred p;\nsetp.ne.b32 p, %69, 0;\n"
  "wgmma.mma_async.sync.aligned.m64n128k16.f32.bf16.bf16 {%0, %1, %2, %3, %4, %5, %6, %7, %8, %9, %10, %11, %12, %13, %14, %15, %16, %17, %18, %19, %20, %21, %22, %23, %24, %25, %26, %27, %28, %29, %30, %31, %32, %33, %34, %35, %36, %37, %38, %39, %40, %41, %42, %43, %44, %45, %46, %47, %48, %49, %50, %51, %52, %53, %54, %55, %56, %57, %58, %59, %60, %61, %62, %63}, {%64, %65, %66, %67}, %68, p, 1, 1, 1;\n}\n"
  : "+f"(d[0]), "+f"(d[1]), "+f"(d[2]), "+f"(d[3]), "+f"(d[4]), "+f"(d[5]), "+f"(d[6]), "+f"(d[7]), "+f"(d[8]), "+f"(d[9]), "+f"(d[10]), "+f"(d[11]), "+f"(d[12]), "+f"(d[13]), "+f"(d[14]), "+f"(d[15]), "+f"(d[16]), "+f"(d[17]), "+f"(d[18]), "+f"(d[19]), "+f"(d[20]), "+f"(d[21]), "+f"(d[22]), "+f"(d[23]), "+f"(d[24]), "+f"(d[25]), "+f"(d[26]), "+f"(d[27]), "+f"(d[28]), "+f"(d[29]), "+f"(d[30]), "+f"(d[31]), "+f"(d[32]), "+f"(d[33]), "+f"(d[34]), "+f"(d[35]), "+f"(d[36]), "+f"(d[37]), "+f"(d[38]), "+f"(d[39]), "+f"(d[40]), "+f"(d[41]), "+f"(d[42]), "+f"(d[43]), "+f"(d[44]), "+f"(d[45]), "+f"(d[46]), "+f"(d[47]), "+f"(d[48]), "+f"(d[49]), "+f"(d[50]), "+f"(d[51]), "+f"(d[52]), "+f"(d[53]), "+f"(d[54]), "+f"(d[55]), "+f"(d[56]), "+f"(d[57]), "+f"(d[58]), "+f"(d[59]), "+f"(d[60]), "+f"(d[61]), "+f"(d[62]), "+f"(d[63]) : "r"(a0), "r"(a1), "r"(a2), "r"(a3), "l"(db), "r"(scale_d));
}
__device__ __forceinline__ void wgmma_rs_n112(float (&d)[56], uint32_t a0, uint32_t a1, uint32_t a2, uint32_t a3, uint64_t db, int scale_d) {
  asm volatile("{\n.reg .pred p;\nsetp.ne.b32 p, %61, 0;\n"
  "wgmma.mma_async.sync.aligned.m64n112k16.f32.bf16.bf16 {%0, %1, %2, %3, %4, %5, %6, %7, %8, %9, %10, %11, %12, %13, %14, %15, %16, %17, %18, %19, %20, %21, %22, %23, %24, %25, %26, %27, %28, %29, %30, %31, %32, %33, %34, %35, %36, %37, %38, %39, %40, %41, %42, %43, %44, %45, %46, %47, %48, %49, %50, %51, %52, %53, %54, %55}, {%56, %57, %58, %59}, %60, p, 1, 1, 1;\n}\n"
  : "+f"(d[0]), "+f"(d[1]), "+f"(d[2]), "+f"(d[3]), "+f"(d[4]), "+f"(d[5]), "+f"(d[6]), "+f"(d[7]), "+f"(d[8]), "+f"(d[9]), "+f"(d[10]), "+f"(d[11]), "+f"(d[12]), "+f"(d[13]), "+f"(d[14]), "+f"(d[15]), "+f"(d[16]), "+f"(d[17]), "+f"(d[18]), "+f"(d[19]), "+f"(d[20]), "+f"(d[21]), "+f"(d[22]), "+f"(d[23]), "+f"(d[24]), "+f"(d[25]), "+f"(d[26]), "+f"(d[27]), "+f"(d[28]), "+f"(d[29]), "+f"(d[30]), "+f"(d[31]), "+f"(d[32]), "+f"(d[33]), "+f"(d[34]), "+f"(d[35]), "+f"(d[36]), "+f"(d[37]), "+f"(d[38]), "+f"(d[39]), "+f"(d[40]), "+f"(d[41]), "+f"(d[42]), "+f"(d[43]), "+f"(d[44]), "+f"(d[45]), "+f"(d[46]), "+f"(d[47]), "+f"(d[48]), "+f"(d[49]), "+f"(d[50]), "+f"(d[51]), "+f"(d[52]), "+f"(d[53]), "+f"(d[54]), "+f"(d[55]) : "r"(a0), "r"(a1), "r"(a2), "r"(a3), "l"(db), "r"(scale_d));
}
__device__ __forceinline__ void wgmma_rs_n64t(float (&d)[32], uint32_t a0, uint32_t a1, uint32_t a2, uint32_t a3, uint64_t db, int scale_d) {
  asm volatile("{\n.reg .pred p;\nsetp.ne.b32 p, %37, 0;\n"
  "wgmma.mma_async.sync.aligned.m64n64k16.f32.bf16.bf16 {%0, %1, %2, %3, %4, %5, %6, %7, %8, %9, %10, %11, %12, %13, %14, %15, %16, %17, %18, %19, %20, %21, %22, %23, %24, %25, %26, %27, %28, %29, %30, %31}, {%32, %33, %34, %35}, %36, p, 1, 1, 1;\n}\n"
  : "+f"(d[0]), "+f"(d[1]), "+f"(d[2]), "+f"(d[3]), "+f"(d[4]), "+f"(d[5]), "+f"(d[6]), "+f"(d[7]), "+f"(d[8]), "+f"(d[9]), "+f"(d[10]), "+f"(d[11]), "+f"(d[12]), "+f"(d[13]), "+f"(d[14]), "+f"(d[15]), "+f"(d[16]), "+f"(d[17]), "+f"(d[18]), "+f"(d[19]), "+f"(d[20]), "+f"(d[21]), "+f"(d[22]), "+f"(d[23]), "+f"(d[24]), "+f"(d[25]), "+f"(d[26]), "+f"(d[27]), "+f"(d[28]), "+f"(d[29]), "+f"(d[30]), "+f"(d[31]) : "r"(a0), "r"(a1), "r"(a2), "r"(a3), "l"(db), "r"(scale_d));
}
__device__ __forceinline__ void wgmma_rs_n64(float (&d)[32], uint32_t a0, uint32_t a1, uint32_t a2, uint32_t a3, uint64_t db, int scale_d) {
  asm volatile("{\n.reg .pred p;\nsetp.ne.b32 p, %37, 0;\n"
  "wgmma.mma_async.sync.aligned.m64n64k16.f32.bf16.bf16 {%0, %1, %2, %3, %4, %5, %6, %7, %8, %9, %10, %11, %12, %13, %14, %15, %16, %17, %18, %19, %20, %21, %22, %23, %24, %25, %26, %27, %28, %29, %30, %31}, {%32, %33, %34, %35}, %36, p, 1, 1, 0;\n}\n"
  : "+f"(d[0]), "+f"(d[1]), "+f"(d[2]), "+f"(d[3]), "+f"(d[4]), "+f"(d[5]), "+f"(d[6]), "+f"(d[7]), "+f"(d[8]), "+f"(d[9]), "+f"(d[10]), "+f"(d[11]), "+f"(d[12]), "+f"(d[13]), "+f"(d[14]), "+f"(d[15]), "+f"(d[16]), "+f"(d[17]), "+f"(d[18]), "+f"(d[19]), "+f"(d[20]), "+f"(d[21]), "+f"(d[22]), "+f"(d[23]), "+f"(d[24]), "+f"(d[25]), "+f"(d[26]), "+f"(d[27]), "+f"(d[28]), "+f"(d[29]), "+f"(d[30]), "+f"(d[31]) : "r"(a0), "r"(a1), "r"(a2), "r"(a3), "l"(db), "r"(scale_d));
}
__device__ __forceinline__ void wgmma_rs_n72(float (&d)[36], uint32_t a0, uint32_t a1, uint32_t a2, uint32_t a3, uint64_t db, int scale_d) {
  asm volatile("{\n.reg .pred p;\nsetp.ne.b32 p, %41, 0;\n"
  "wgmma.mma_async.sync.aligned.m64n72k16.f32.bf16.bf16 {%0, %1, %2, %3, %4, %5, %6, %7, %8, %9, %10, %11, %12, %13, %14, %15, %16, %17, %18, %19, %20, %21, %22, %23, %24, %25, %26, %27, %28, %29, %30, %31, %32, %33, %34, %35}, {%36, %37, %38, %39}, %40, p, 1, 1, 0;\n}\n"
  : "+f"(d[0]), "+f"(d[1]), "+f"(d[2]), "+f"(d[3]), "+f"(d[4]), "+f"(d[5]), "+f"(d[6]), "+f"(d[7]), "+f"(d[8]), "+f"(d[9]), "+f"(d[10]), "+f"(d[11]), "+f"(d[12]), "+f"(d[13]), "+f"(d[14]), "+f"(d[15]), "+f"(d[16]), "+f"(d[17]), "+f"(d[18]), "+f"(d[19]), "+f"(d[20]), "+f"(d[21]), "+f"(d[22]), "+f"(d[23]), "+f"(d[24]), "+f"(d[25]), "+f"(d[26]), "+f"(d[27]), "+f"(d[28]), "+f"(d[29]), "+f"(d[30]), "+f"(d[31]), "+f"(d[32]), "+f"(d[33]), "+f"(d[34]), "+f"(d[35]) : "r"(a0), "r"(a1), "r"(a2), "r"(a3), "l"(db), "r"(scale_d));
}

namespace {

constexpr int S_ = 2048, D_ = 512, F_ = 1376;

constexpr uint32_t OFF_XN   = 0;
constexpr uint32_t OFF_STG  = 0;
constexpr uint32_t STG_V    = 16864;
constexpr uint32_t OFF_KVB  = 0;
constexpr uint32_t OFF_KVRAW = 18432;
constexpr uint32_t OFF_XS_RECV = 0;
constexpr uint32_t OFF_XO_RECV = 32768;
constexpr uint32_t OFF_WPHI = 13 * 16384;
constexpr uint32_t OFF_MISC = 14 * 16384;
constexpr uint32_t OFF_BAR  = OFF_MISC;
constexpr uint32_t SMEM_BYTES = OFF_MISC + 3072;

constexpr int B_FULL = 0, B_EMPTY = 14;
constexpr int B_RDY = 28;
constexpr int B_KV = 40, B_HA = 41, B_HB = 42, B_HC = 43, B_O = 44;
constexpr int B_KVDONE = 45, B_KVB = 46, B_XO_OK = 47, B_XS_OK = 48, B_XO_FULL = 49, B_XS_FULL = 51;
constexpr int B_WPHI = 53, B_XNL = 54, B_XNR = 55, B_XLAND = 56, B_KVRAW = 57, B_XNFREE = 58, B_SKEW = 59;
constexpr int B_XNL2 = 64;
constexpr int NBAR = 65;

#define TILE_TBL {8, 9, 10, 11, 12, 4, 5, 6, 7, 56, 57, 58, 59, 60, 52, 53, 54, 55, 40, 41, 42, 43, 44, 36, 37, 38, 39, 2, 3, 56, 57, 58, 59, 60, 52, 53, 54, 55, 50, 51, 40, 41, 42, 43, 44, 36, 37, 38, 0, 1, 13, 39}
__device__ __constant__ unsigned char c_tile[52] = TILE_TBL;
__host__ __device__ constexpr int tile_ent(int t) { constexpr unsigned char tb[52] = TILE_TBL; return tb[t]; }

__device__ __align__(1024) unsigned char g_ha[16 * 8 * 16384];
__device__ __align__(1024) unsigned char g_hb[16 * 8 * 16384];
__device__ __align__(1024) unsigned char g_hc[16 * 8 * 12288];
__device__ __align__(1024) unsigned char g_o [16 * 8 * 16384];
__device__ __align__(1024) float g_kv[2][32 * 512];
__device__ __align__(1024) float g_z [2][32 * 32];
__device__ unsigned int g_flag_ha[128 * 8];
__device__ unsigned int g_flag_hb[128 * 8];
__device__ unsigned int g_flag_hc[128 * 8];
__device__ unsigned int g_flag_o [128 * 8];
__device__ unsigned int g_kvcnt[8 * 8];
__device__ unsigned int g_epoch;
__device__ unsigned int g_done;

#define MARK(i)
#define TRC(i)
#define TRP(i)
#define TRL(i)

struct TMaps {
  CUtensorMap kv, q, w1, w3, w2, w2t, wo, out;
};

__device__ __forceinline__ uint32_t smem_u32(const void* p) { return (uint32_t)__cvta_generic_to_shared(p); }
__device__ __forceinline__ void mbar_init(uint32_t bar, int cnt) { asm volatile("mbarrier.init.shared::cta.b64 [%0], %1;" ::"r"(bar), "r"(cnt)); }
__device__ __forceinline__ void mbar_expect_tx(uint32_t bar, uint32_t bytes) { asm volatile("mbarrier.arrive.expect_tx.shared::cta.b64 _, [%0], %1;" ::"r"(bar), "r"(bytes) : "memory"); }
__device__ __forceinline__ void mbar_arrive(uint32_t bar) { asm volatile("mbarrier.arrive.shared::cta.b64 _, [%0];" ::"r"(bar) : "memory"); }
__device__ __forceinline__ void mbar_wait(uint32_t bar, uint32_t parity) {
  asm volatile("{\n.reg .pred p;\n.reg .u64 t, d;\n.reg .u32 a;\n"
               "mbarrier.test_wait.parity.shared::cta.b64 p, [%0], %1;\n@p bra WAIT_DONE;\n"
               "WAIT_LOOP:\nmbarrier.try_wait.parity.shared::cta.b64 p, [%0], %1, 100000;\n@p bra WAIT_DONE;\n"
               "and.b32 a, %0, 0xFFFFFC00;\nld.shared.u64 d, [a + 1016];\nmov.u64 t, %%globaltimer;\nsetp.lt.u64 p, t, d;\n@p bra WAIT_LOOP;\nWAIT_DONE:\n}\n" ::"r"(bar), "r"(parity) : "memory");
}
__device__ __forceinline__ void mbar_wait_cluster(uint32_t bar, uint32_t parity) {
  asm volatile("{\n.reg .pred p;\n.reg .u64 t, d;\n.reg .u32 a;\n"
               "WAIT_LOOP:\nmbarrier.try_wait.parity.acquire.cluster.shared::cta.b64 p, [%0], %1, 100000;\n@p bra WAIT_DONE;\n"
               "and.b32 a, %0, 0xFFFFFC00;\nld.shared.u64 d, [a + 1016];\nmov.u64 t, %%globaltimer;\nsetp.lt.u64 p, t, d;\n@p bra WAIT_LOOP;\nWAIT_DONE:\n}\n" ::"r"(bar), "r"(parity) : "memory");
}
__device__ __forceinline__ unsigned long long gtime() { unsigned long long t; asm volatile("mov.u64 %0, %%globaltimer;" : "=l"(t)); return t; }
__device__ __forceinline__ uint32_t mapa(uint32_t addr, uint32_t cta) { uint32_t r; asm volatile("mapa.shared::cluster.u32 %0, %1, %2;" : "=r"(r) : "r"(addr), "r"(cta)); return r; }
__device__ __forceinline__ void mbar_arrive_remote(uint32_t raddr) { asm volatile("mbarrier.arrive.shared::cluster.b64 _, [%0];" ::"r"(raddr) : "memory"); }
__device__ __forceinline__ void tma2d(uint32_t dst, const CUtensorMap* tm, int c0, int c1, uint32_t bar) {
  asm volatile("cp.async.bulk.tensor.2d.shared::cluster.global.mbarrier::complete_tx::bytes [%0], [%1, {%3, %4}], [%2];" ::"r"(dst), "l"(tm), "r"(bar), "r"(c0), "r"(c1) : "memory");
}
__device__ __forceinline__ void tma3d(uint32_t dst, const CUtensorMap* tm, int c0, int c1, int c2, uint32_t bar) {
  asm volatile("cp.async.bulk.tensor.3d.shared::cluster.global.mbarrier::complete_tx::bytes [%0], [%1, {%3, %4, %5}], [%2];" ::"r"(dst), "l"(tm), "r"(bar), "r"(c0), "r"(c1), "r"(c2) : "memory");
}
__device__ __forceinline__ void bulk_g2s(uint32_t dst, const void* src, uint32_t bytes, uint32_t bar) {
  asm volatile("cp.async.bulk.shared::cluster.global.mbarrier::complete_tx::bytes [%0], [%1], %2, [%3];" ::"r"(dst), "l"(src), "r"(bytes), "r"(bar) : "memory");
}
__device__ __forceinline__ void bulk_red_add_f32(void* dst, uint32_t src, uint32_t bytes) {
  asm volatile("cp.reduce.async.bulk.global.shared::cta.bulk_group.add.f32 [%0], [%1], %2;" ::"l"(dst), "r"(src), "r"(bytes) : "memory");
}
__device__ __forceinline__ void bulk_commit() { asm volatile("cp.async.bulk.commit_group;" ::: "memory"); }
__device__ __forceinline__ void bulk_wait0() { asm volatile("cp.async.bulk.wait_group 0;" ::: "memory"); }
__device__ __forceinline__ void fence_async_smem() { asm volatile("fence.proxy.async.shared::cta;" ::: "memory"); }
__device__ __forceinline__ void red_release_gpu(unsigned int* p, unsigned int v) { asm volatile("red.release.gpu.global.add.u32 [%0], %1;" ::"l"(p), "r"(v) : "memory"); }
__device__ __forceinline__ unsigned int ld_acquire_gpu(const unsigned int* p) { unsigned int v; asm volatile("ld.acquire.gpu.global.u32 %0, [%1];" : "=r"(v) : "l"(p) : "memory"); return v; }
__device__ __forceinline__ void wg_fence() { asm volatile("wgmma.fence.sync.aligned;" ::: "memory"); }
__device__ __forceinline__ void wg_commit() { asm volatile("wgmma.commit_group.sync.aligned;" ::: "memory"); }
template <int N> __device__ __forceinline__ void wg_wait() { asm volatile("wgmma.wait_group.sync.aligned %0;" ::"n"(N) : "memory"); }
__device__ __forceinline__ void named_bar(int id, int n) { asm volatile("bar.sync %0, %1;" ::"r"(id), "r"(n) : "memory"); }
__device__ __forceinline__ uint64_t mkdesc(uint32_t addr, uint32_t lbo, uint32_t sbo, uint32_t mode) {
  return (uint64_t)((addr & 0x3FFFF) >> 4) | ((uint64_t)(lbo >> 4) << 16) | ((uint64_t)(sbo >> 4) << 32) | ((uint64_t)mode << 62);
}
__device__ __forceinline__ uint32_t pack_bf16(float lo, float hi) { uint32_t r; asm("cvt.rn.bf16x2.f32 %0, %1, %2;" : "=r"(r) : "f"(hi), "f"(lo)); return r; }
__device__ __forceinline__ float bf_lo(uint32_t v) { return __uint_as_float(v << 16); }
__device__ __forceinline__ float bf_hi(uint32_t v) { return __uint_as_float(v & 0xFFFF0000u); }
__device__ __forceinline__ float ex2(float x) { float r; asm("ex2.approx.ftz.f32 %0, %1;" : "=f"(r) : "f"(x)); return r; }
__device__ __forceinline__ float rcp(float x) { float r; asm("rcp.approx.ftz.f32 %0, %1;" : "=f"(r) : "f"(x)); return r; }
__device__ __forceinline__ float tanh_a(float x) { float r; asm("tanh.approx.f32 %0, %1;" : "=f"(r) : "f"(x)); return r; }
__device__ __forceinline__ float silu_mul(float g, float u) { float hg = 0.5f * g; float a = hg * u; return fmaf(a, tanh_a(hg), a); }
__device__ __forceinline__ void stsm4(uint32_t addr, uint32_t r0, uint32_t r1, uint32_t r2, uint32_t r3) {
  asm volatile("stmatrix.sync.aligned.m8n8.x4.shared.b16 [%0], {%1, %2, %3, %4};" ::"r"(addr), "r"(r0), "r"(r1), "r"(r2), "r"(r3) : "memory");
}
__device__ __forceinline__ void sts32(uint32_t a, uint32_t v) { asm volatile("st.shared.u32 [%0], %1;" ::"r"(a), "r"(v) : "memory"); }
__device__ __forceinline__ void sts16(uint32_t a, unsigned short v) { asm volatile("st.shared.u16 [%0], %1;" ::"r"(a), "h"(v) : "memory"); }
__device__ __forceinline__ void sts128(uint32_t a, uint4 v) { asm volatile("st.shared.v4.u32 [%0], {%1,%2,%3,%4};" ::"r"(a), "r"(v.x), "r"(v.y), "r"(v.z), "r"(v.w) : "memory"); }
__device__ __forceinline__ float4 lds128f(uint32_t a) { float4 v; asm volatile("ld.shared.v4.f32 {%0,%1,%2,%3}, [%4];" : "=f"(v.x), "=f"(v.y), "=f"(v.z), "=f"(v.w) : "r"(a) : "memory"); return v; }
__device__ __forceinline__ void st_async4(uint32_t raddr, float a, float b, float c, float d, uint32_t rbar) {
  asm volatile("st.async.weak.shared::cluster.mbarrier::complete_tx::bytes.v4.f32 [%0], {%1,%2,%3,%4}, [%5];" ::"r"(raddr), "f"(a), "f"(b), "f"(c), "f"(d), "r"(rbar) : "memory");
}
__device__ __forceinline__ uint4 ldg128(const void* p) { uint4 v; asm volatile("ld.global.nc.L1::no_allocate.v4.u32 {%0,%1,%2,%3}, [%4];" : "=r"(v.x), "=r"(v.y), "=r"(v.z), "=r"(v.w) : "l"(p)); return v; }

constexpr float LOG2E = 1.4426950408889634f;

__device__ __forceinline__ void tma5d(uint32_t dst, const CUtensorMap* tm, int c0, int c1, int c2, int c3, int c4, uint32_t bar) {
  asm volatile("cp.async.bulk.tensor.5d.shared::cluster.global.mbarrier::complete_tx::bytes [%0], [%1, {%3, %4, %5, %6, %7}], [%2];"
               ::"r"(dst), "l"(tm), "r"(bar), "r"(c0), "r"(c1), "r"(c2), "r"(c3), "r"(c4) : "memory");
}
__device__ __forceinline__ void tma_store2d(const CUtensorMap* tm, uint32_t src, int c0, int c1) {
  asm volatile("cp.async.bulk.tensor.2d.global.shared::cta.bulk_group [%0, {%2, %3}], [%1];" ::"l"(tm), "r"(src), "r"(c0), "r"(c1) : "memory");
}
__device__ __forceinline__ void stg128(void* p, uint32_t a, uint32_t b, uint32_t c, uint32_t d) {
  asm volatile("st.global.v4.u32 [%0], {%1,%2,%3,%4};" ::"l"(p), "r"(a), "r"(b), "r"(c), "r"(d) : "memory");
}
__device__ __forceinline__ uint4 ldcg128(const void* p) { uint4 v; asm volatile("ld.global.cg.v4.u32 {%0,%1,%2,%3}, [%4];" : "=r"(v.x), "=r"(v.y), "=r"(v.z), "=r"(v.w) : "l"(p) : "memory"); return v; }
__device__ __forceinline__ void ldsm4(uint32_t addr, uint32_t& r0, uint32_t& r1, uint32_t& r2, uint32_t& r3) {
  asm volatile("ldmatrix.sync.aligned.m8n8.x4.shared.b16 {%0, %1, %2, %3}, [%4];" : "=r"(r0), "=r"(r1), "=r"(r2), "=r"(r3) : "r"(addr) : "memory");
}
__device__ __forceinline__ void sts64(uint32_t a, uint32_t x, uint32_t y) { asm volatile("st.shared.v2.u32 [%0], {%1, %2};" ::"r"(a), "r"(x), "r"(y) : "memory"); }
__device__ __forceinline__ uint32_t mbar_test(uint32_t bar, uint32_t parity) {
  uint32_t ok;
  asm volatile("{\n.reg .pred p;\nmbarrier.test_wait.parity.shared::cta.b64 p, [%1], %2;\nselp.u32 %0, 1, 0, p;\n}\n" : "=r"(ok) : "r"(bar), "r"(parity) : "memory");
  return ok;
}
__device__ __forceinline__ void st_async4u(uint32_t raddr, uint4 v, uint32_t rbar) {
  asm volatile("st.async.weak.shared::cluster.mbarrier::complete_tx::bytes.v4.b32 [%0], {%1,%2,%3,%4}, [%5];" ::"r"(raddr), "r"(v.x), "r"(v.y), "r"(v.z), "r"(v.w), "r"(rbar) : "memory");
}
#define KEEPF(x) asm volatile("" ::"f"(x))

template <int I>
__device__ __forceinline__ void row_sm(const float (&p)[32], uint32_t (&o)[16]) {
  float mx = fmaxf(p[2 * I], p[2 * I + 1]), mn = fminf(p[2 * I], p[2 * I + 1]);
#pragma unroll
  for (int j = 1; j < 8; j++) {
    mx = fmaxf(mx, fmaxf(p[4 * j + 2 * I], p[4 * j + 2 * I + 1]));
    mn = fminf(mn, fminf(p[4 * j + 2 * I], p[4 * j + 2 * I + 1]));
  }
  const float mxl = -mx * LOG2E, mnl = mn * LOG2E;
  float e[16], f[16];
  float sp0 = 0.f, sp1 = 0.f, sn0 = 0.f, sn1 = 0.f;
#pragma unroll
  for (int j = 0; j < 8; j++) {
    e[2 * j] = ex2(fmaf(p[4 * j + 2 * I], LOG2E, mxl));      e[2 * j + 1] = ex2(fmaf(p[4 * j + 2 * I + 1], LOG2E, mxl));
    f[2 * j] = ex2(fmaf(p[4 * j + 2 * I], -LOG2E, mnl));     f[2 * j + 1] = ex2(fmaf(p[4 * j + 2 * I + 1], -LOG2E, mnl));
    sp0 += e[2 * j]; sp1 += e[2 * j + 1]; sn0 += f[2 * j]; sn1 += f[2 * j + 1];
  }
  const float rp = rcp(sp0 + sp1), rn = rcp(sn0 + sn1);
#pragma unroll
  for (int j = 0; j < 8; j++) {
    o[j] = pack_bf16(e[2 * j] * rp, e[2 * j + 1] * rp);
    o[8 + j] = pack_bf16(f[2 * j] * rn, f[2 * j + 1] * rn);
  }
}

#define POLLNS 64
#define SKEW_TILES 4
template <int NV>
__device__ __forceinline__ void pass_rs(float (&acc)[NV / 2], const uint32_t (&xa)[128], int t0, uint32_t sb, uint32_t bar0, int lane, bool lead) {
  const uint64_t dB0 = mkdesc(sb, 8192, 1024, 1);
  uint32_t prev = 0;
  if (!lead) mbar_wait(bar0 + 8u * B_SKEW + t0, 0);
#pragma unroll
  for (int c = 0; c < 8; c++) {
    const uint32_t e = c_tile[t0 + c], slot = e & 15u;
    mbar_wait(bar0 + 8u * (B_FULL + slot), (e >> 4) & 1u);
    const uint64_t dB = dB0 + (uint64_t)(slot * 1024u);
    wg_fence();
#pragma unroll
    for (int k = 0; k < 4; k++) {
      const int i = 16 * c + 4 * k;
      if constexpr (NV == 128) wgmma_rs_n128(acc, xa[i], xa[i + 1], xa[i + 2], xa[i + 3], dB + 128 * k, (c > 0 || k > 0) ? 1 : 0);
      else wgmma_rs_n112(acc, xa[i], xa[i + 1], xa[i + 2], xa[i + 3], dB + 128 * k, (c > 0 || k > 0) ? 1 : 0);
    }
    wg_commit();
    if (c > 0) { wg_wait<1>(); if (lane == 0) mbar_arrive(bar0 + 8u * (B_EMPTY + prev)); }
    if (c == SKEW_TILES && lead && lane == 0) mbar_arrive(bar0 + 8u * B_SKEW + t0);
    prev = slot;
  }
  wg_wait<0>();
  if (lane == 0) mbar_arrive(bar0 + 8u * (B_EMPTY + prev));
}

template <int N, int NK, int FIRST, int OFF, int NF>
__device__ __forceinline__ void rs_step(float (&acc)[64], const uint4 (&f)[NF], uint32_t sb, uint32_t bar0, int lane) {
  constexpr int e = tile_ent(36 + N);
  mbar_wait(bar0 + 8u * (B_FULL + (e & 15)), (e >> 4) & 1);
  const uint64_t dB = mkdesc(sb + (uint32_t)(e & 15) * 16384u, 8192, 1024, 1);
  wg_fence();
#pragma unroll
  for (int k = 0; k < NK; k++) wgmma_rs_n128(acc, f[OFF + k].x, f[OFF + k].y, f[OFF + k].z, f[OFF + k].w, dB + 128 * k, (FIRST && k == 0) ? 0 : 1);
  if (N & 1) {
    wg_commit();
    if (N >= 3 && N <= 13) {
      wg_wait<1>();
      if (N <= 9 && lane == 0) {
        mbar_arrive(bar0 + 8u * (B_EMPTY + (tile_ent(36 + (N >= 3 ? N - 3 : 0)) & 15)));
        mbar_arrive(bar0 + 8u * (B_EMPTY + (tile_ent(36 + (N >= 3 ? N - 2 : 0)) & 15)));
      }
    }
  }
}
template <int N0, int N1>
__device__ __forceinline__ void rel_steps(uint32_t bar0, int lane) {
  if (lane == 0) {
#pragma unroll
    for (int n = N0; n < N1; n++) mbar_arrive(bar0 + 8u * (B_EMPTY + (tile_ent(36 + n) & 15)));
  }
}
template <int NK, int OFF, int NF>
__device__ __forceinline__ void fetch_tile(uint4 (&f)[NF], const unsigned char* base, int id, int wg, int tw, uint32_t wb) {
  mbar_wait(wb, 0);
  const unsigned char* p = base + ((size_t)(id * 2 + wg) * NK * 128 + tw) * 16;
#pragma unroll
  for (int k = 0; k < NK; k++) f[OFF + k] = ldcg128(p + k * 2048);
}

__host__ __device__ constexpr int bar_count(int i) {
  return (i >= B_EMPTY && i < B_EMPTY + 14) ? 8 : (i >= B_KV && i <= B_O) ? 256 : (i == B_KVB || i == B_WPHI) ? 32
       : (i == B_XNFREE || i == B_XNL2) ? 4 : (i == B_XO_OK || i == B_XS_OK || i == B_XLAND) ? 8 : (i == B_XNL) ? 256 : (i >= B_SKEW) ? 4 : 1;
}
template <int LO, int HI>
__device__ __forceinline__ void init_bars(uint32_t bar0) {
#pragma unroll
  for (int i = LO; i < HI; i++) mbar_init(bar0 + 8u * i, bar_count(i));
}

__device__ __forceinline__ void teardown(bool leader) {
  if (leader) {
    unsigned int tk = atomicAdd(&g_done, 1u);
    if ((tk & 127u) == 127u) { atomicAdd(&g_epoch, 1u); }
  }
}

#define REIDS() \
  int tid_, bid_; asm volatile("mov.u32 %0, %%tid.x;" : "=r"(tid_)); asm volatile("mov.u32 %0, %%ctaid.x;" : "=r"(bid_)); \
  const int lane = tid_ & 31, wg = tid_ >> 7, w4 = (tid_ >> 5) & 3, g = lane >> 2, t4 = lane & 3, tw = tid_ & 127; \
  const int m = bid_ >> 3, nq = (bid_ >> 1) & 3, kh = bid_ & 1; const uint32_t peer = (uint32_t)(kh ^ 1); \
  const size_t tile_id = (size_t)(m * 8 + kh * 4 + nq) * 2 + wg; \
  (void)g; (void)t4; (void)w4; (void)peer; (void)tile_id; (void)tw; (void)nq;

__global__ void __cluster_dims__(2, 1, 1) __launch_bounds__(384, 1)
fused_kernel(const __grid_constant__ TMaps tm, const __nv_bfloat16* __restrict__ x, const __nv_bfloat16* __restrict__ wphi,
             __nv_bfloat16* __restrict__ out) {
  extern __shared__ __align__(1024) unsigned char smem_raw[];
  const uint32_t sb = smem_u32(smem_raw);
  const int tid = threadIdx.x;
  const int warp = __shfl_sync(0xffffffffu, tid >> 5, 0), lane = tid & 31;
  const int bid = blockIdx.x;
  const int m = bid >> 3, r = bid & 7, nq = r >> 1, kh = r & 1;
  const int sl = kh * 4 + nq;
  const int f0 = kh * 688 + nq * 176;
  const uint32_t bar0 = sb + OFF_BAR;
  auto BAR = [&](int i) { return bar0 + 8u * (uint32_t)i; };
  if (warp < 8) MARK(29);

  uint4 v[8], vn[8];
  if (warp < 8) {
    const __nv_bfloat16* xb = x + (size_t)(m * 128 + kh * 64 + warp * 8 + (lane >> 3)) * D_ + (lane & 7) * 8;
#pragma unroll
    for (int i = 0; i < 8; i++) v[i] = ldg128(xb + i * 64);
#pragma unroll
    for (int i = 0; i < 8; i++) vn[i] = ldg128(xb + 4 * D_ + i * 64);
  }
  if (tid == 383) asm volatile("st.shared.u64 [%0 + 1016], %1;" ::"r"(bar0), "l"(gtime() + 20000000ull) : "memory");
  if (warp >= 8 && lane == 0) {
    if (warp == 8) init_bars<0, 15>(bar0);
    else if (warp == 9) init_bars<15, 30>(bar0);
    else if (warp == 10) init_bars<30, 45>(bar0);
    else {
      init_bars<45, NBAR>(bar0);
      mbar_expect_tx(BAR(B_XNR), 65536);
#pragma unroll
      for (int i = 0; i < 4; i++) mbar_expect_tx(BAR(B_XO_FULL + i), 16384);
    }
    asm volatile("fence.mbarrier_init.release.cluster;" ::: "memory");
  }
  __syncthreads();
  asm volatile("barrier.cluster.arrive.relaxed.aligned;" ::: "memory");

  if (warp >= 8) {
    asm volatile("setmaxnreg.dec.sync.aligned.u32 24;");
    asm volatile("barrier.cluster.wait.aligned;" ::: "memory");
    if (warp == 8 || warp == 10) {
      if (lane == 0) {
        MARK(0);
        const bool second = (warp == 10);
        const int colb = nq * 128 + (second ? (kh ^ 1) : kh) * 64;
        mbar_wait(BAR(B_XLAND), 0);
#pragma unroll 1
        for (int t = 0; t < 52; t++) {
          const uint32_t e = c_tile[t], slot = e & 15u;
          if (e & 32u) mbar_wait(BAR(B_EMPTY + slot), ((e >> 4) & 1u) ^ 1u);
          else if (slot < 2 || slot == 13) mbar_wait(BAR(B_O), 0);
          else if (slot < 4) mbar_wait(BAR(B_KVDONE), 0);
          else if (slot < 8) mbar_wait(BAR(B_XNFREE), 0);
          const uint32_t fb = BAR(B_FULL + slot), dst = sb + slot * 16384u + (second ? 8192u : 0u);
          if (t < 8) {
            if (!second) { mbar_expect_tx(fb, 16384); tma3d(dst, &tm.kv, sl * 64, t * 64, 1, fb); }
          } else if (t < 32) {
            if (!second) mbar_expect_tx(fb, 16384);
            tma2d(dst, second ? &tm.w3 : &tm.w1, f0 + ((t - 8) >> 3) * 64, (t & 7) * 64, fb);
          } else if (t < 36) {
            if (!second) { mbar_expect_tx(fb, 16384); tma2d(dst, &tm.q, sl * 64, (t - 32) * 128, fb); }
          } else {
            const int n = t - 36, grp = n >> 2, q = (nq + n) & 3;
            if (!second) mbar_expect_tx(fb, grp == 2 ? 12288u : 16384u);
            if (grp == 3) tma5d(dst, &tm.wo, colb, 0, (kh * 4 + q) * 4, 0, 0, fb);
            else tma2d(dst, grp == 2 ? &tm.w2t : &tm.w2, colb, kh * 688 + q * 176 + grp * 64, fb);
          }
        }
        MARK(5);
      }
    } else if (warp == 9) {
      if (lane == 0) {
        const unsigned int epoch = *(volatile unsigned int*)&g_epoch;
        const int id = m * 8 + sl;
#pragma unroll 1
        for (int job = 0; job < 5; job++) {
          mbar_wait(BAR(B_KV + job), 0);
          if (job == 0) {
#pragma unroll 1
            for (int w = 0; w < 2; w++) {
              bulk_red_add_f32(&g_kv[epoch & 1][sl * 2048], sb + OFF_STG + w * 32768, 8192);
              bulk_red_add_f32(&g_z[epoch & 1][sl * 128], sb + OFF_STG + w * 32768 + 8192, 512);
            }
            bulk_commit(); bulk_wait0();
            red_release_gpu(g_kvcnt + sl * 8, 1);
            mbar_arrive(BAR(B_KVDONE));
          } else {
            red_release_gpu((job == 1 ? g_flag_ha : (job == 2 ? g_flag_hb : (job == 3 ? g_flag_hc : g_flag_o))) + id * 8, 1);
          }
          MARK(1 + job);
        }
        teardown(true);
      }
    } else {
      {
#pragma unroll 4
        for (int i = lane; i < 512; i += 32) sts128(sb + OFF_WPHI + i * 16, make_uint4(0u, 0u, 0u, 0u));
        __syncwarp();
        const unsigned short* wp = reinterpret_cast<const unsigned short*>(wphi) + sl * 4 * 256;
#pragma unroll 4
        for (int i = lane; i < 1024; i += 32) {
          int h = i >> 8, d = (i >> 4) & 15, f = i & 15;
          sts16(sb + OFF_WPHI + h * 2048 + (f >> 1) * 256 + (d >> 3) * 128 + (2 * h + (f & 1)) * 16 + (d & 7) * 2, wp[i]);
        }
        fence_async_smem();
        mbar_arrive(BAR(B_WPHI));
      }
      const unsigned int epoch = *(volatile unsigned int*)&g_epoch;
      reinterpret_cast<float4*>(&g_kv[(epoch + 1) & 1][bid * 128])[lane] = make_float4(0.f, 0.f, 0.f, 0.f);
      if (lane < 8) g_z[(epoch + 1) & 1][bid * 8 + lane] = 0.f;
      __syncwarp();
      const int grp = lane / 3, d = lane - grp * 3 + 1;
      const int id = m * 8 + kh * 4 + ((nq + d) & 3);
      const unsigned int* flag = (grp == 0 ? g_flag_ha : (grp == 1 ? g_flag_hb : (grp == 2 ? g_flag_hc : g_flag_o))) + id * 8;
      unsigned int tgt = epoch + 1u;
      if (lane == 12) { flag = g_kvcnt + sl * 8; tgt = 16u * (epoch + 1u); }
      int state = lane <= 12 ? 0 : 2;
      while (true) {
        bool kvgo = false;
        if (state == 0 && (int)(ld_acquire_gpu(flag) - tgt) >= 0) {
          if (lane < 12) { mbar_arrive(BAR(B_RDY + lane)); state = 2; }
          else {
            mbar_expect_tx(BAR(B_KVRAW), 8704);
            bulk_g2s(sb + OFF_KVRAW, &g_kv[epoch & 1][sl * 2048], 8192, BAR(B_KVRAW));
            bulk_g2s(sb + OFF_KVRAW + 8192, &g_z[epoch & 1][sl * 128], 512, BAR(B_KVRAW));
            state = 1; kvgo = true;
          }
        }
        if (__ballot_sync(0xffffffffu, kvgo)) {
#pragma unroll 4
          for (int i = lane; i < 1152; i += 32) sts128(sb + OFF_KVB + i * 16, make_uint4(0u, 0u, 0u, 0u));
          __syncwarp();
        }
        if (__ballot_sync(0xffffffffu, state == 1 && mbar_test(BAR(B_KVRAW), 0))) {
          MARK(1);
#pragma unroll 2
          for (int i = lane; i < 512; i += 32) {
            float4 w = lds128f(sb + OFF_KVRAW + i * 16);
            const int h = i >> 7, dd = (i >> 3) & 15, st = i & 7;
            const uint32_t a = sb + OFF_KVB + st * 2304 + (dd >> 1) * 256 + (2 * h + (dd & 1)) * 16 + h * 4;
            sts32(a, pack_bf16(w.x, w.y));
            sts32(a + 128, pack_bf16(w.z, w.w));
          }
          {
            float4 w = lds128f(sb + OFF_KVRAW + 8192 + lane * 16);
            const int h = lane >> 3, st = lane & 7;
            const uint32_t a = sb + OFF_KVB + st * 2304 + 2048 + 2 * h * 16 + h * 4;
            const uint32_t z0 = pack_bf16(w.x, w.y), z1 = pack_bf16(w.z, w.w);
            sts32(a, z0); sts32(a + 16, z0); sts32(a + 128, z1); sts32(a + 144, z1);
          }
          fence_async_smem();
          mbar_arrive(BAR(B_KVB));
          if (lane == 12) state = 2;
          MARK(3);
        }
        if (__all_sync(0xffffffffu, state == 2)) break;
        unsigned long long dl; asm volatile("ld.shared.u64 %0, [%1 + 1016];" : "=l"(dl) : "r"(bar0) : "memory");
        if (gtime() >= dl) break;
        __nanosleep(POLLNS);
      }
      MARK(2);
    }
  } else {
    asm volatile("setmaxnreg.inc.sync.aligned.u32 240;");
    MARK(0);
    const int wg = warp >> 2, w4 = warp & 3;
    const int g = lane >> 2, t4 = lane & 3;
    const int tw = tid & 127;
    const uint32_t peer = (uint32_t)(kh ^ 1);
    {
      const int rsub = lane >> 3, sub = lane & 7;
      const int row0 = warp * 8 + rsub;
      asm volatile("barrier.cluster.wait.aligned;" ::: "memory");
      const uint32_t rbar = mapa(BAR(B_XNR), peer);
      const uint32_t rsb = mapa(sb, peer);
#pragma unroll 1
      for (int gi = 0; gi < 2; gi++) {
        float s = 0.f;
#pragma unroll
        for (int i = 0; i < 8; i++) {
          s += (bf_lo(v[i].x) + bf_hi(v[i].x)) + (bf_lo(v[i].y) + bf_hi(v[i].y));
          s += (bf_lo(v[i].z) + bf_hi(v[i].z)) + (bf_lo(v[i].w) + bf_hi(v[i].w));
        }
        s += __shfl_xor_sync(0xffffffffu, s, 1);
        s += __shfl_xor_sync(0xffffffffu, s, 2);
        s += __shfl_xor_sync(0xffffffffu, s, 4);
        if (gi == 0 && lane == 0) mbar_arrive(BAR(B_XLAND));
        MARK(16 + gi);
        const float mean = s * (1.f / 512.f);
        float q0 = 0.f, q1 = 0.f;
#pragma unroll
        for (int i = 0; i < 8; i++) {
          const uint32_t* w = reinterpret_cast<const uint32_t*>(&v[i]);
#pragma unroll
          for (int e = 0; e < 4; e++) {
            float d0 = bf_lo(w[e]) - mean, d1 = bf_hi(w[e]) - mean;
            q0 = fmaf(d0, d0, q0); q1 = fmaf(d1, d1, q1);
          }
        }
        float q = q0 + q1;
        q += __shfl_xor_sync(0xffffffffu, q, 1);
        q += __shfl_xor_sync(0xffffffffu, q, 2);
        q += __shfl_xor_sync(0xffffffffu, q, 4);
        const float rstd = rsqrtf(q * (1.f / 512.f) + 1e-5f);
        const float nb = -mean * rstd;
        const int row = row0 + gi * 4;
        const uint32_t ro = OFF_XN + row * 128 + ((sub ^ (row & 7)) << 4);
#pragma unroll
        for (int i = 0; i < 8; i++) {
          const uint32_t* w = reinterpret_cast<const uint32_t*>(&v[i]);
          uint4 o;
          o.x = pack_bf16(fmaf(bf_lo(w[0]), rstd, nb), fmaf(bf_hi(w[0]), rstd, nb));
          o.y = pack_bf16(fmaf(bf_lo(w[1]), rstd, nb), fmaf(bf_hi(w[1]), rstd, nb));
          o.z = pack_bf16(fmaf(bf_lo(w[2]), rstd, nb), fmaf(bf_hi(w[2]), rstd, nb));
          o.w = pack_bf16(fmaf(bf_lo(w[3]), rstd, nb), fmaf(bf_hi(w[3]), rstd, nb));
          st_async4u(rsb + ro + i * 8192, o, rbar);
          sts128(sb + 65536 + ro + i * 8192, o);
          v[i] = vn[i];
        }
      }
      mbar_arrive(BAR(B_XNL));
      if (wg == kh) mbar_wait(BAR(B_XNL), 0); else mbar_wait_cluster(BAR(B_XNR), 0);
    }
    MARK(1);
    uint4 fo[4], f0[16], f1[16];
    {
      uint32_t xa[128];
      {
        const int row = w4 * 16 + (lane & 7) + ((lane >> 3) & 1) * 8;
        const uint32_t ra = sb + OFF_XN + (wg == kh ? 65536 : 0) + row * 128, sw = row & 7, hi = lane >> 4;
#pragma unroll
        for (int j = 0; j < 32; j++)
          ldsm4(ra + (j >> 2) * 8192 + ((((j & 3) * 2 + hi) ^ sw) << 4), xa[4 * j], xa[4 * j + 1], xa[4 * j + 2], xa[4 * j + 3]);
        fence_async_smem();
        __syncwarp();
        if (lane == 0) mbar_arrive(BAR(wg == kh ? B_XNFREE : B_XNL2));
      }
      const bool lead = (wg == kh);
#pragma unroll 1
      for (int ps = 0; ps < 3; ps++) {
        float acc[64];
        pass_rs<128>(acc, xa, 8 * ps, sb, bar0, lane, lead);
        MARK(2 + 2 * ps);
        REIDS();
        if (ps == 0) {
          const uint32_t stg = sb + OFF_STG + wg * 32768;
          float p[32];
          {
            uint32_t kp[16];
#pragma unroll
            for (int i = 0; i < 16; i++) kp[i] = pack_bf16(acc[2 * i], acc[2 * i + 1]);
            mbar_wait(BAR(B_XNL2), 0);
            const uint32_t vsa = stg + STG_V + (uint32_t)((2 * w4 + ((lane >> 3) & 1)) * 128 + (lane >> 4) * 1024 + (lane & 7) * 16);
#pragma unroll
            for (int o = 0; o < 4; o++)
              stsm4(vsa + o * 2048, pack_bf16(acc[32 + 8 * o], acc[33 + 8 * o]), pack_bf16(acc[34 + 8 * o], acc[35 + 8 * o]),
                    pack_bf16(acc[36 + 8 * o], acc[37 + 8 * o]), pack_bf16(acc[38 + 8 * o], acc[39 + 8 * o]));
            sts64(stg + STG_V + 8192 + tw * 8, 0x3F803F80u, 0x3F803F80u);
            mbar_wait(BAR(B_WPHI), 0);
            wg_fence();
#pragma unroll
            for (int h = 0; h < 4; h++) wgmma_rs_n64(p, kp[4 * h], kp[4 * h + 1], kp[4 * h + 2], kp[4 * h + 3], mkdesc(sb + OFF_WPHI, 128, 256, 0) + h * 128, h > 0);
            wg_commit();
            wg_wait<0>();
          }
          const uint32_t pka = stg + t4 * 1056 + 2 * w4 * 128 + g * 16;
          {
            uint32_t ra[16];
            row_sm<0>(p, ra);
#pragma unroll
            for (int o = 0; o < 4; o++) sts128(pka + o * 4224, make_uint4(ra[4 * o], ra[4 * o + 1], ra[4 * o + 2], ra[4 * o + 3]));
            row_sm<1>(p, ra);
#pragma unroll
            for (int o = 0; o < 4; o++) sts128(pka + o * 4224 + 128, make_uint4(ra[4 * o], ra[4 * o + 1], ra[4 * o + 2], ra[4 * o + 3]));
          }
          fence_async_smem();
          named_bar(1 + wg, 128);
          float d0[36], d1[36];
          const uint64_t dPK = mkdesc(stg, 128, 1056, 0), dV = mkdesc(stg + STG_V, 128, 1024, 0);
          wg_fence();
#pragma unroll
          for (int ks = 0; ks < 4; ks++) {
            wgmma_n72_tt(d0, dPK + ks * 16, dV + ks * 16, ks > 0);
            wgmma_n72_tt(d1, dPK + 528 + ks * 16, dV + ks * 16, ks > 0);
          }
          wg_commit();
          wg_wait<0>();
          named_bar(1 + wg, 128);
          const bool od = (w4 & 1) != 0;
          const uint32_t a = stg + (w4 & 1) * 4096 + t4 * 256 + ((w4 >> 1) * 8 + g) * 4;
#pragma unroll
          for (int i = 0; i < 2; i++)
#pragma unroll
            for (int jj = 0; jj < 2; jj++)
#pragma unroll
              for (int e = 0; e < 2; e++) {
                const int rr = (2 * i + jj) * 4 + 2 * i + e;
                const uint32_t o = (uint32_t)(i * 2048 + jj * 1024 + e * 128);
                sts32(a + o, __float_as_uint(od ? d0[16 + rr] : d0[rr]));
                sts32(a + o + 64, __float_as_uint(od ? d1[16 + rr] : d1[rr]));
              }
#pragma unroll
          for (int e = 0; e < 36; e++) { KEEPF(d0[e]); KEEPF(d1[e]); }
          if (t4 == 0) {
            const uint32_t za = stg + 8192 + (w4 & 1) * 256 + ((w4 >> 1) * 8 + g) * 4;
            sts32(za, __float_as_uint(d0[32]));        sts32(za + 128, __float_as_uint(d0[34]));
            sts32(za + 64, __float_as_uint(d1[32]));   sts32(za + 128 + 64, __float_as_uint(d1[34]));
          }
          fence_async_smem();
          mbar_arrive(BAR(B_KV));
        } else {
          unsigned char* gp = (ps == 1 ? g_ha : g_hb) + (tile_id * 512 + tw) * 16;
#pragma unroll
          for (int i = 0; i < 4; i++)
            stg128(gp + i * 2048, pack_bf16(silu_mul(acc[8 * i], acc[32 + 8 * i]), silu_mul(acc[8 * i + 1], acc[33 + 8 * i])),
                   pack_bf16(silu_mul(acc[8 * i + 2], acc[34 + 8 * i]), silu_mul(acc[8 * i + 3], acc[35 + 8 * i])),
                   pack_bf16(silu_mul(acc[8 * i + 4], acc[36 + 8 * i]), silu_mul(acc[8 * i + 5], acc[37 + 8 * i])),
                   pack_bf16(silu_mul(acc[8 * i + 6], acc[38 + 8 * i]), silu_mul(acc[8 * i + 7], acc[39 + 8 * i])));
          mbar_arrive(BAR(B_KV + ps));
        }
        MARK(3 + 2 * ps);
      }
      {
        float acc[56];
        pass_rs<112>(acc, xa, 24, sb, bar0, lane, lead);
        REIDS();
#pragma unroll
        for (int e = 24; e < 32; e++) KEEPF(acc[e]);
        unsigned char* gp = g_hc + (tile_id * 384 + tw) * 16;
#pragma unroll
        for (int i = 0; i < 3; i++) {
          uint32_t w0 = pack_bf16(silu_mul(acc[8 * i], acc[32 + 8 * i]), silu_mul(acc[8 * i + 1], acc[33 + 8 * i]));
          uint32_t w1 = pack_bf16(silu_mul(acc[8 * i + 2], acc[34 + 8 * i]), silu_mul(acc[8 * i + 3], acc[35 + 8 * i]));
          uint32_t w2 = pack_bf16(silu_mul(acc[8 * i + 4], acc[36 + 8 * i]), silu_mul(acc[8 * i + 5], acc[37 + 8 * i]));
          uint32_t w3 = pack_bf16(silu_mul(acc[8 * i + 6], acc[38 + 8 * i]), silu_mul(acc[8 * i + 7], acc[39 + 8 * i]));
          if (i == 2 && nq == 3) { w0 = 0u; w1 = 0u; w2 = 0u; w3 = 0u; }
          stg128(gp + i * 2048, w0, w1, w2, w3);
        }
        mbar_arrive(BAR(B_HC));
      }
      MARK(8);
      {
        float aq[32];
        if (!lead) mbar_wait(BAR(B_SKEW + 4), 0);
#pragma unroll
        for (int c = 0; c < 4; c++) {
          constexpr int dummy = 0; (void)dummy;
          const uint32_t e = c_tile[32 + c], slot = e & 15u;
          mbar_wait(BAR(B_FULL + slot), (e >> 4) & 1u);
          const uint64_t dB = mkdesc(sb + slot * 16384u, 8192, 1024, 1);
          wg_fence();
#pragma unroll
          for (int k = 0; k < 8; k++) {
            const int i = 32 * c + 4 * k;
            wgmma_rs_n64t(aq, xa[i], xa[i + 1], xa[i + 2], xa[i + 3], dB + 128 * k, (c > 0 || k > 0) ? 1 : 0);
          }
          wg_commit();
          if (c == 3 && lead && lane == 0) mbar_arrive(BAR(B_SKEW + 4));
        }
        wg_wait<0>();
        if (lane == 0) {
#pragma unroll
          for (int c = 0; c < 4; c++) mbar_arrive(BAR(B_EMPTY + (tile_ent(32 + c) & 15)));
        }
        MARK(9);
        REIDS();
        float p[32];
        uint32_t qp[16];
#pragma unroll
        for (int i = 0; i < 16; i++) qp[i] = pack_bf16(aq[2 * i], aq[2 * i + 1]);
        wg_fence();
#pragma unroll
        for (int h = 0; h < 4; h++) wgmma_rs_n64(p, qp[4 * h], qp[4 * h + 1], qp[4 * h + 2], qp[4 * h + 3], mkdesc(sb + OFF_WPHI, 128, 256, 0) + h * 128, h > 0);
        wg_commit();
        wg_wait<0>();
        {
          const int idb = m * 8 + kh * 4;
          fetch_tile<4, 0>(f0, g_ha, idb + nq, wg, tw, BAR(B_HA));
          fetch_tile<4, 4>(f0, g_ha, idb + ((nq + 1) & 3), wg, tw, BAR(B_RDY + 0));
          fetch_tile<4, 8>(f0, g_ha, idb + ((nq + 2) & 3), wg, tw, BAR(B_RDY + 1));
          fetch_tile<4, 12>(f0, g_ha, idb + ((nq + 3) & 3), wg, tw, BAR(B_RDY + 2));
        }
        uint32_t ra[16], rb[16];
        row_sm<0>(p, ra);
        row_sm<1>(p, rb);
        float nd[36];
        const uint64_t dKV = mkdesc(sb + OFF_KVB, 128, 256, 0);
        mbar_wait(BAR(B_KVB), 0);
        wg_fence();
#pragma unroll
        for (int st = 0; st < 8; st++) wgmma_rs_n72(nd, ra[2 * st], rb[2 * st], ra[2 * st + 1], rb[2 * st + 1], dKV + st * 144, st > 0);
        wg_commit();
        wg_wait<0>();
        const float r0 = rcp(0.5f * (nd[32] + nd[33]) + 1e-6f), r1 = rcp(0.5f * (nd[34] + nd[35]) + 1e-6f);
        unsigned char* gp = g_o + (tile_id * 512 + tw) * 16;
#pragma unroll
        for (int b = 0; b < 4; b++) {
          fo[b].x = pack_bf16(nd[8 * b] * r0, nd[8 * b + 1] * r0);      fo[b].y = pack_bf16(nd[8 * b + 2] * r1, nd[8 * b + 3] * r1);
          fo[b].z = pack_bf16(nd[8 * b + 4] * r0, nd[8 * b + 5] * r0);  fo[b].w = pack_bf16(nd[8 * b + 6] * r1, nd[8 * b + 7] * r1);
          stg128(gp + b * 2048, fo[b].x, fo[b].y, fo[b].z, fo[b].w);
        }
        mbar_arrive(BAR(B_O));
      }
    }
    MARK(10);
    {
      REIDS();
      float a_o[64], a_s[64];
      const int idb = m * 8 + kh * 4;
      const int id0 = idb + nq, id1 = idb + ((nq + 1) & 3), id2 = idb + ((nq + 2) & 3), id3 = idb + ((nq + 3) & 3);
      uint4 f2[12], f3[12];
      rs_step<0, 4, 1, 0>(a_o, f0, sb, bar0, lane);
      rs_step<1, 4, 0, 4>(a_o, f0, sb, bar0, lane);
      rs_step<2, 4, 0, 8>(a_o, f0, sb, bar0, lane);
      rs_step<3, 4, 0, 12>(a_o, f0, sb, bar0, lane);
        {
          fetch_tile<4, 0>(f1, g_hb, idb + nq, wg, tw, BAR(B_HB));
          fetch_tile<4, 4>(f1, g_hb, idb + ((nq + 1) & 3), wg, tw, BAR(B_RDY + 3));
          fetch_tile<4, 8>(f1, g_hb, idb + ((nq + 2) & 3), wg, tw, BAR(B_RDY + 4));
          fetch_tile<4, 12>(f1, g_hb, idb + ((nq + 3) & 3), wg, tw, BAR(B_RDY + 5));
        }
      MARK(11);
      rs_step<4, 4, 0, 0>(a_o, f1, sb, bar0, lane);
      rs_step<5, 4, 0, 4>(a_o, f1, sb, bar0, lane);
      if (lane == 0) mbar_arrive_remote(mapa(BAR(B_XO_OK), peer));
      rs_step<6, 4, 0, 8>(a_o, f1, sb, bar0, lane);
      rs_step<7, 4, 0, 12>(a_o, f1, sb, bar0, lane);
      fetch_tile<3, 0>(f2, g_hc, id0, wg, tw, BAR(B_HC));
      fetch_tile<3, 3>(f2, g_hc, id1, wg, tw, BAR(B_RDY + 6));
      fetch_tile<3, 6>(f2, g_hc, id2, wg, tw, BAR(B_RDY + 7));
      fetch_tile<3, 9>(f2, g_hc, id3, wg, tw, BAR(B_RDY + 8));
      MARK(12);
      rs_step<8, 3, 0, 0>(a_o, f2, sb, bar0, lane);
      rs_step<9, 3, 0, 3>(a_o, f2, sb, bar0, lane);
      rs_step<10, 3, 0, 6>(a_o, f2, sb, bar0, lane);
      rs_step<11, 3, 0, 9>(a_o, f2, sb, bar0, lane);
      fetch_tile<4, 0>(f3, g_o, id1, wg, tw, BAR(B_RDY + 9));
      fetch_tile<4, 4>(f3, g_o, id2, wg, tw, BAR(B_RDY + 10));
      fetch_tile<4, 8>(f3, g_o, id3, wg, tw, BAR(B_RDY + 11));
      MARK(13);
      rs_step<12, 4, 1, 0>(a_s, fo, sb, bar0, lane);
      rs_step<13, 4, 0, 0>(a_s, f3, sb, bar0, lane);
      rs_step<14, 4, 0, 4>(a_s, f3, sb, bar0, lane);
      rs_step<15, 4, 0, 8>(a_s, f3, sb, bar0, lane);
      {
        mbar_wait_cluster(BAR(B_XO_OK), 0);
        uint32_t ra = mapa(sb + OFF_XO_RECV + wg * 16384 + tw * 16, peer), rb = mapa(BAR(B_XO_FULL + wg), peer);
#pragma unroll
        for (int i = 0; i < 8; i++) st_async4(ra + i * 2048, a_o[32 + 4 * i], a_o[33 + 4 * i], a_o[34 + 4 * i], a_o[35 + 4 * i], rb);
      }
      wg_wait<1>();
      if (lane == 0) mbar_arrive_remote(mapa(BAR(B_XS_OK), peer));
      uint32_t xr[16];
      {
        const uint32_t* xp = reinterpret_cast<const uint32_t*>(x + (size_t)(m * 128 + wg * 64 + w4 * 16 + g) * D_ + nq * 128 + kh * 64 + t4 * 2);
#pragma unroll
        for (int j = 0; j < 8; j++) { xr[2 * j] = __ldg(xp + j * 4); xr[2 * j + 1] = __ldg(xp + 8 * (D_ / 2) + j * 4); }
      }
      mbar_wait_cluster(BAR(B_XO_FULL + wg), 0);
      float gt[32];
#pragma unroll
      for (int i = 0; i < 8; i++) {
        float4 w = lds128f(sb + OFF_XO_RECV + wg * 16384 + tw * 16 + i * 2048);
        gt[4 * i] = silu_mul(a_o[4 * i] + w.x, 1.f); gt[4 * i + 1] = silu_mul(a_o[4 * i + 1] + w.y, 1.f);
        gt[4 * i + 2] = silu_mul(a_o[4 * i + 2] + w.z, 1.f); gt[4 * i + 3] = silu_mul(a_o[4 * i + 3] + w.w, 1.f);
      }
      wg_wait<0>();
      MARK(14);
      {
        mbar_wait_cluster(BAR(B_XS_OK), 0);
        uint32_t ra = mapa(sb + OFF_XS_RECV + wg * 16384 + tw * 16, peer), rb = mapa(BAR(B_XS_FULL + wg), peer);
#pragma unroll
        for (int i = 0; i < 8; i++) st_async4(ra + i * 2048, a_s[32 + 4 * i], a_s[33 + 4 * i], a_s[34 + 4 * i], a_s[35 + 4 * i], rb);
      }
      named_bar(1 + wg, 128);
      const int orow = w4 * 16 + (lane & 7) + ((lane >> 3) & 1) * 8;
      const uint32_t oa = sb + OFF_XO_RECV + wg * 16384 + orow * 128;
      mbar_wait_cluster(BAR(B_XS_FULL + wg), 0);
#pragma unroll
      for (int i = 0; i < 8; i += 2) {
        uint32_t y[4];
#pragma unroll
        for (int u = 0; u < 2; u++) {
          float4 w = lds128f(sb + OFF_XS_RECV + wg * 16384 + tw * 16 + (i + u) * 2048);
          const int b = 4 * (i + u);
          y[2 * u] = pack_bf16(fmaf(a_s[b] + w.x, gt[b], bf_lo(xr[2 * (i + u)])), fmaf(a_s[b + 1] + w.y, gt[b + 1], bf_hi(xr[2 * (i + u)])));
          y[2 * u + 1] = pack_bf16(fmaf(a_s[b + 2] + w.z, gt[b + 2], bf_lo(xr[2 * (i + u) + 1])), fmaf(a_s[b + 3] + w.w, gt[b + 3], bf_hi(xr[2 * (i + u) + 1])));
        }
        stsm4(oa + (uint32_t)(((i + (lane >> 4)) ^ (orow & 7)) << 4), y[0], y[1], y[2], y[3]);
      }
      fence_async_smem();
      named_bar(1 + wg, 128);
      if (tw == 0) {
        tma_store2d(&tm.out, sb + OFF_XO_RECV + wg * 16384, nq * 128 + kh * 64, m * 128 + wg * 64);
        bulk_commit();
        asm volatile("cp.async.bulk.wait_group.read 0;" ::: "memory");
      }
    }
    MARK(15);
  }
}

typedef CUresult (*EncFn)(CUtensorMap*, CUtensorMapDataType, cuuint32_t, void*, const cuuint64_t*, const cuuint64_t*, const cuuint32_t*,
                          const cuuint32_t*, CUtensorMapInterleave, CUtensorMapSwizzle, CUtensorMapL2promotion, CUtensorMapFloatOOBfill);

void enc(EncFn fn, CUtensorMap* tm, const void* base, int rank, const cuuint64_t* gd, const cuuint64_t* gs, const cuuint32_t* bd) {
  cuuint32_t es[5] = {1, 1, 1, 1, 1};
  CUresult rc = fn(tm, CU_TENSOR_MAP_DATA_TYPE_BFLOAT16, (cuuint32_t)rank, const_cast<void*>(base), gd, gs, bd, es, CU_TENSOR_MAP_INTERLEAVE_NONE,
                   CU_TENSOR_MAP_SWIZZLE_128B, CU_TENSOR_MAP_L2_PROMOTION_L2_128B, CU_TENSOR_MAP_FLOAT_OOB_FILL_NONE);
  (void)rc;
}

}

extern "C" void kernel_launch(void* const* d_in, const int* in_sizes, int n_in, void* d_out, int out_size) {
  const __nv_bfloat16* x    = (const __nv_bfloat16*)d_in[0];
  const __nv_bfloat16* wqkv = (const __nv_bfloat16*)d_in[1];
  const __nv_bfloat16* wphi = (const __nv_bfloat16*)d_in[2];
  const __nv_bfloat16* wo   = (const __nv_bfloat16*)d_in[3];
  const __nv_bfloat16* w1   = (const __nv_bfloat16*)d_in[5];
  const __nv_bfloat16* w3   = (const __nv_bfloat16*)d_in[6];
  const __nv_bfloat16* w2   = (const __nv_bfloat16*)d_in[7];

  static EncFn fn = nullptr;
  if (!fn) {
    void* p = nullptr; cudaDriverEntryPointQueryResult qr;
    cudaGetDriverEntryPoint("cuTensorMapEncodeTiled", &p, cudaEnableDefault, &qr);
    fn = (EncFn)p;
    cudaFuncSetAttribute(fused_kernel, cudaFuncAttributeMaxDynamicSharedMemorySize, SMEM_BYTES);
  }
  TMaps tm;
  { cuuint64_t gd[3] = {512, 512, 3}; cuuint64_t gs[2] = {3072, 1024}; cuuint32_t bd[3] = {64, 64, 2};
    enc(fn, &tm.kv, wqkv, 3, gd, gs, bd); }
  { cuuint64_t gd[2] = {1536, 512}; cuuint64_t gs[1] = {3072}; cuuint32_t bd[2] = {64, 128};
    enc(fn, &tm.q, wqkv, 2, gd, gs, bd); }
  { cuuint64_t gd[2] = {F_, 512}; cuuint64_t gs[1] = {F_ * 2}; cuuint32_t bd[2] = {64, 64};
    enc(fn, &tm.w1, w1, 2, gd, gs, bd);  enc(fn, &tm.w3, w3, 2, gd, gs, bd); }
  { cuuint64_t gd[2] = {512, 2048}; cuuint64_t gs[1] = {1024}; cuuint32_t bd[2] = {64, 64};
    enc(fn, &tm.out, d_out, 2, gd, gs, bd); }
  { cuuint64_t gd[2] = {512, F_}; cuuint64_t gs[1] = {1024}; cuuint32_t bd[2] = {64, 64}; cuuint32_t bd2[2] = {64, 48};
    enc(fn, &tm.w2, w2, 2, gd, gs, bd); enc(fn, &tm.w2t, w2, 2, gd, gs, bd2); }
  {
    cuuint64_t gd[5] = {512, 2, 32, 2, 4}; cuuint64_t gs[4] = {1024, 16384, 2048, 4096}; cuuint32_t bd[5] = {64, 2, 4, 2, 4};
    enc(fn, &tm.wo, wo, 5, gd, gs, bd); }

  cudaLaunchConfig_t cfg = {};
  cfg.gridDim = dim3(128); cfg.blockDim = dim3(384); cfg.dynamicSmemBytes = SMEM_BYTES; cfg.stream = cudaStreamPerThread;
  cudaLaunchKernelEx(&cfg, fused_kernel, tm, x, wphi, (__nv_bfloat16*)d_out);
}
```
